```python
import torch

def _softmax(x, axis=-1):
    return torch.softmax(x, dim=axis)
def _gelu(x):
    return torch.nn.functional.gelu(x, approximate="tanh")
def _silu(x):
    return torch.nn.functional.silu(x)
def _sigmoid(x):
    return torch.sigmoid(x)
def _layernorm(x, axis=-1, eps=1e-5):
    m = x.mean(dim=axis, keepdim=True)
    v = x.var(dim=axis, keepdim=True, unbiased=False)
    return (x - m) / torch.sqrt(v + eps)
def _scatter_add(tgt, idx, src, axis=0):
    return tgt.clone().index_add_(axis, idx, src)
def _segment_sum(src, seg, n):
    out = torch.zeros((n,) + src.shape[1:], dtype=src.dtype)
    return out.index_add_(0, seg, src)
def _pad(x, pw):
    flat = tuple(v for pair in reversed(pw) for v in pair)
    return torch.nn.functional.pad(x, flat)

kernel_name = 'gated_mix__linear_attn_block__ssm_conv_s4d__prompt'

def setup_inputs():

    _w = (lambda a: (lambda t: t.to(torch.bfloat16) if t.is_floating_point() else t)(torch.as_tensor(a)))
    def _A_setup():
        B, S, D = 1, 2048, 1024
        return {
            "x": _w((lambda *s: torch.randn(*s, dtype=torch.bfloat16) * 0.05)(B, S, D)),
            "wqkv": _w((lambda *s: torch.randn(*s, dtype=torch.bfloat16) * 0.8)(D, 3 * D)),
            "wo": _w((lambda *s: torch.randn(*s, dtype=torch.bfloat16) * 0.05)(D, D)),
        }
    _A_in = _A_setup()

    def _B_setup():
        Bsz, L, D, N = 1, 2048, 1024, 128
        return {
            "u": _w((lambda *s: torch.randn(*s, dtype=torch.bfloat16) * 0.05)(Bsz, L, D)),
            "log_A_real": _w((lambda *s: torch.randn(*s, dtype=torch.bfloat16) * 3.2)(D, N) * 0.5),
            "A_imag": _w((lambda *s: torch.randn(*s, dtype=torch.bfloat16) * 0.05)(D, N) * 3.14),
            "C_real": _w((lambda *s: torch.randn(*s, dtype=torch.bfloat16) * 0.8)(D, N) / N ** 0.5),
            "C_imag": _w((lambda *s: torch.randn(*s, dtype=torch.bfloat16) * 0.8)(D, N) / N ** 0.5),
            "log_dt": _w((lambda *s: torch.randn(*s, dtype=torch.bfloat16) * 0.05)(D) * 0.5 - 4.0),
            "D_skip": _w((lambda *s: torch.randn(*s, dtype=torch.bfloat16) * 0.1)(D)),
        }
    _B_in = _B_setup()

    return {
        "A_x": _A_in["x"],
        "A_wqkv": _A_in["wqkv"],
        "A_wo": _A_in["wo"],
        "B_u": _B_in["u"],
        "B_log_A_real": _B_in["log_A_real"],
        "B_A_imag": _B_in["A_imag"],
        "B_C_real": _B_in["C_real"],
        "B_C_imag": _B_in["C_imag"],
        "B_log_dt": _B_in["log_dt"],
        "B_D_skip": _B_in["D_skip"],
        "gate_w": _w((lambda *s: torch.randn(*s, dtype=torch.bfloat16) * 0.05)(1024) * 16.0),
    }

def reference(A_x, A_wqkv, A_wo, B_u, B_log_A_real, B_A_imag, B_C_real, B_C_imag, B_log_dt, B_D_skip, gate_w):
    def _A_ref(x, wqkv, wo):
        B, S, D = x.shape
        H = 32; Dh = D // H
        qkv = (lambda x, *d: x.permute(*d))((x @ wqkv).reshape(B, S, 3, H, Dh), 2, 0, 3, 1, 4)
        q, k, v = qkv[0], qkv[1], qkv[2]
        phi = lambda t: torch.where(t > 0, t + 1, torch.exp(t)) + 1e-6
        pq, pk = phi(q), phi(k)
        kv = torch.einsum("bhsd,bhse->bhde", pk, v)
        z = torch.einsum("bhsd->bhd", pk)
        num = torch.einsum("bhqd,bhde->bhqe", pq, kv)
        den = torch.einsum("bhqd,bhd->bhq", pq, z)[..., None] + 1e-6
        o = num / den
        return (lambda x, *d: x.permute(*d))(o, 0, 2, 1, 3).reshape(B, S, D) @ wo

    def _B_ref(u, log_A_real, A_imag, C_real, C_imag, log_dt, D_skip):
        L = u.shape[1]
        dt = torch.exp(log_dt)
        A = -torch.exp(log_A_real) + 1j * A_imag
        C = (C_real + 1j * C_imag) * dt[:, None]
        pos = (lambda x, dt: x.to(dt))(torch.arange(L), log_dt.dtype)
        P = torch.exp((A * dt[:, None])[:, :, None] * pos[None, None, :])
        K = 2.0 * torch.einsum("dn,dnl->dl", C, P).real
        L2 = 2 * L
        u_t = (lambda x, *d: x.permute(*d))(u, 0, 2, 1)
        Kf = (lambda x, *a, **k: torch.fft.rfft(x.float(), *a, **k))(K, L2)
        Uf = (lambda x, *a, **k: torch.fft.rfft(x.float(), *a, **k))(u_t, L2)
        y = (lambda x, *a, **k: torch.fft.irfft(x, *a, **k).to(torch.bfloat16))(Uf * Kf[None, :, :], L2)[:, :, :L]
        y = (lambda x, *d: x.permute(*d))(y, 0, 2, 1)
        return y + u * D_skip[None, None, :]

    x = A_x
    g = _sigmoid((x * gate_w).sum(-1, keepdims=True))
    a = _A_ref(x, A_wqkv, A_wo)
    b = _B_ref(x, B_log_A_real, B_A_imag, B_C_real, B_C_imag, B_log_dt, B_D_skip)
    return g * a + (1 - g) * b
```

```cpp
#include <cuda_runtime.h>
#include <cuda_bf16.h>
#include <cuda.h>
#include <stdint.h>

typedef __nv_bfloat16 bf16;

constexpr int SEQ = 2048, DM = 1024, NMODE = 128;

__device__ __align__(1024) bf16 g_o[SEQ * DM];
__device__ __align__(1024) bf16 g_b[SEQ * DM];
__device__ float g_gate[SEQ];
__device__ __align__(16) float g_part[16 * 8 * 2 * 1056];
__device__ unsigned int g_cnt[16];

__device__ __forceinline__ uint32_t smem_u32(const void* p) { return (uint32_t)__cvta_generic_to_shared(p); }
__device__ __forceinline__ void mbar_init(uint32_t bar, uint32_t cnt) {
  asm volatile("mbarrier.init.shared::cta.b64 [%0], %1;" ::"r"(bar), "r"(cnt));
}
__device__ __forceinline__ void mbar_expect_tx(uint32_t bar, uint32_t bytes) {
  asm volatile("mbarrier.arrive.expect_tx.shared::cta.b64 _, [%0], %1;" ::"r"(bar), "r"(bytes) : "memory");
}
__device__ __forceinline__ void mbar_arrive_cluster(uint32_t bar, uint32_t cta) {
  asm volatile(
      "{\n.reg .b32 ra;\nmapa.shared::cluster.u32 ra, %0, %1;\n"
      "mbarrier.arrive.release.cluster.shared::cluster.b64 _, [ra];\n}\n" ::"r"(bar), "r"(cta) : "memory");
}
__device__ __forceinline__ bool mbar_try_wait(uint32_t bar, uint32_t parity) {
  uint32_t ok;
  asm volatile(
      "{\n.reg .pred p;\nmbarrier.try_wait.parity.shared::cta.b64 p, [%1], %2;\nselp.u32 %0, 1, 0, p;\n}\n"
      : "=r"(ok) : "r"(bar), "r"(parity) : "memory");
  return ok;
}
__device__ __forceinline__ void mbar_wait(uint32_t bar, uint32_t parity) {
  while (!mbar_try_wait(bar, parity)) {}
}
__device__ __forceinline__ void tma_load_2d(uint32_t dst, const CUtensorMap* map, uint32_t bar, int c0, int c1) {
  asm volatile(
      "cp.async.bulk.tensor.2d.shared::cluster.global.mbarrier::complete_tx::bytes [%0], [%1, {%3, %4}], [%2];" ::"r"(dst),
      "l"(map), "r"(bar), "r"(c0), "r"(c1) : "memory");
}
__device__ __forceinline__ void tma_load_2d_mc(uint32_t dst, const CUtensorMap* map, uint32_t bar, int c0, int c1,
                                               uint16_t mask) {
  asm volatile(
      "cp.async.bulk.tensor.2d.shared::cluster.global.mbarrier::complete_tx::bytes.multicast::cluster [%0], [%1, {%3, %4}], [%2], %5;" ::"r"(dst),
      "l"(map), "r"(bar), "r"(c0), "r"(c1), "h"(mask) : "memory");
}
__device__ __forceinline__ void cluster_sync_all() {
  asm volatile("barrier.cluster.arrive.release.aligned;\nbarrier.cluster.wait.acquire.aligned;\n" ::: "memory");
}
__device__ __forceinline__ uint32_t cluster_ctarank() {
  uint32_t r; asm volatile("mov.u32 %0, %%cluster_ctarank;" : "=r"(r)); return r;
}
__device__ __forceinline__ void named_bar_sync(int id, int n) { asm volatile("bar.sync %0, %1;" ::"r"(id), "r"(n) : "memory"); }
__device__ __forceinline__ void fence_async_smem() { asm volatile("fence.proxy.async.shared::cta;" ::: "memory"); }
__device__ __forceinline__ void wg_fence() { asm volatile("wgmma.fence.sync.aligned;" ::: "memory"); }
__device__ __forceinline__ void wg_commit() { asm volatile("wgmma.commit_group.sync.aligned;" ::: "memory"); }
template <int N> __device__ __forceinline__ void wg_wait() { asm volatile("wgmma.wait_group.sync.aligned %0;" ::"n"(N) : "memory"); }
__device__ __forceinline__ uint64_t make_desc(uint32_t addr, uint32_t lbo, uint32_t sbo) {
  return (uint64_t)((addr & 0x3FFFF) >> 4) | ((uint64_t)(lbo >> 4) << 16) | ((uint64_t)(sbo >> 4) << 32) | (1ull << 62);
}
__device__ __forceinline__ float bfr(float x) { return __bfloat162float(__float2bfloat16_rn(x)); }
__device__ __forceinline__ uint32_t pack2(float lo, float hi) {
  __nv_bfloat162 v = __floats2bfloat162_rn(lo, hi);
  return *reinterpret_cast<uint32_t*>(&v);
}
__device__ __forceinline__ float phi_f(float acc) {
  float t = bfr(acc);
  float f = t > 0.f ? bfr(t + 1.0f) : bfr(expf(t));
  return bfr(f + 1e-6f);
}
template <int R> __device__ __forceinline__ void fence_regs(float (&d)[R]) {
#pragma unroll
  for (int i = 0; i < R; i++) asm volatile("" : "+f"(d[i])::"memory");
}

__device__ __forceinline__ void wgmma_ss_n192_tb(float (&d)[96], uint64_t da, uint64_t db, int sc) {
  asm volatile("{\n.reg .pred p;\nsetp.ne.b32 p, %98, 0;\n"
    "wgmma.mma_async.sync.aligned.m64n192k16.f32.bf16.bf16 {%0, %1, %2, %3, %4, %5, %6, %7, %8, %9, %10, %11, %12, %13, %14, %15, %16, %17, %18, %19, %20, %21, %22, %23, %24, %25, %26, %27, %28, %29, %30, %31, %32, %33, %34, %35, %36, %37, %38, %39, %40, %41, %42, %43, %44, %45, %46, %47, %48, %49, %50, %51, %52, %53, %54, %55, %56, %57, %58, %59, %60, %61, %62, %63, %64, %65, %66, %67, %68, %69, %70, %71, %72, %73, %74, %75, %76, %77, %78, %79, %80, %81, %82, %83, %84, %85, %86, %87, %88, %89, %90, %91, %92, %93, %94, %95}, %96, %97, p, 1, 1, 0, 1;\n}\n"
    : "+f"(d[0]), "+f"(d[1]), "+f"(d[2]), "+f"(d[3]), "+f"(d[4]), "+f"(d[5]), "+f"(d[6]), "+f"(d[7]), "+f"(d[8]), "+f"(d[9]), "+f"(d[10]), "+f"(d[11]), "+f"(d[12]), "+f"(d[13]), "+f"(d[14]), "+f"(d[15]), "+f"(d[16]), "+f"(d[17]), "+f"(d[18]), "+f"(d[19]), "+f"(d[20]), "+f"(d[21]), "+f"(d[22]), "+f"(d[23]), "+f"(d[24]), "+f"(d[25]), "+f"(d[26]), "+f"(d[27]), "+f"(d[28]), "+f"(d[29]), "+f"(d[30]), "+f"(d[31]), "+f"(d[32]), "+f"(d[33]), "+f"(d[34]), "+f"(d[35]), "+f"(d[36]), "+f"(d[37]), "+f"(d[38]), "+f"(d[39]), "+f"(d[40]), "+f"(d[41]), "+f"(d[42]), "+f"(d[43]), "+f"(d[44]), "+f"(d[45]), "+f"(d[46]), "+f"(d[47]), "+f"(d[48]), "+f"(d[49]), "+f"(d[50]), "+f"(d[51]), "+f"(d[52]), "+f"(d[53]), "+f"(d[54]), "+f"(d[55]), "+f"(d[56]), "+f"(d[57]), "+f"(d[58]), "+f"(d[59]), "+f"(d[60]), "+f"(d[61]), "+f"(d[62]), "+f"(d[63]), "+f"(d[64]), "+f"(d[65]), "+f"(d[66]), "+f"(d[67]), "+f"(d[68]), "+f"(d[69]), "+f"(d[70]), "+f"(d[71]), "+f"(d[72]), "+f"(d[73]), "+f"(d[74]), "+f"(d[75]), "+f"(d[76]), "+f"(d[77]), "+f"(d[78]), "+f"(d[79]), "+f"(d[80]), "+f"(d[81]), "+f"(d[82]), "+f"(d[83]), "+f"(d[84]), "+f"(d[85]), "+f"(d[86]), "+f"(d[87]), "+f"(d[88]), "+f"(d[89]), "+f"(d[90]), "+f"(d[91]), "+f"(d[92]), "+f"(d[93]), "+f"(d[94]), "+f"(d[95])
    : "l"(da), "l"(db), "r"(sc));
}

__device__ __forceinline__ void wgmma_ss_n128_tb(float (&d)[64], uint64_t da, uint64_t db, int sc) {
  asm volatile("{\n.reg .pred p;\nsetp.ne.b32 p, %66, 0;\n"
    "wgmma.mma_async.sync.aligned.m64n128k16.f32.bf16.bf16 {%0, %1, %2, %3, %4, %5, %6, %7, %8, %9, %10, %11, %12, %13, %14, %15, %16, %17, %18, %19, %20, %21, %22, %23, %24, %25, %26, %27, %28, %29, %30, %31, %32, %33, %34, %35, %36, %37, %38, %39, %40, %41, %42, %43, %44, %45, %46, %47, %48, %49, %50, %51, %52, %53, %54, %55, %56, %57, %58, %59, %60, %61, %62, %63}, %64, %65, p, 1, 1, 0, 1;\n}\n"
    : "+f"(d[0]), "+f"(d[1]), "+f"(d[2]), "+f"(d[3]), "+f"(d[4]), "+f"(d[5]), "+f"(d[6]), "+f"(d[7]), "+f"(d[8]), "+f"(d[9]), "+f"(d[10]), "+f"(d[11]), "+f"(d[12]), "+f"(d[13]), "+f"(d[14]), "+f"(d[15]), "+f"(d[16]), "+f"(d[17]), "+f"(d[18]), "+f"(d[19]), "+f"(d[20]), "+f"(d[21]), "+f"(d[22]), "+f"(d[23]), "+f"(d[24]), "+f"(d[25]), "+f"(d[26]), "+f"(d[27]), "+f"(d[28]), "+f"(d[29]), "+f"(d[30]), "+f"(d[31]), "+f"(d[32]), "+f"(d[33]), "+f"(d[34]), "+f"(d[35]), "+f"(d[36]), "+f"(d[37]), "+f"(d[38]), "+f"(d[39]), "+f"(d[40]), "+f"(d[41]), "+f"(d[42]), "+f"(d[43]), "+f"(d[44]), "+f"(d[45]), "+f"(d[46]), "+f"(d[47]), "+f"(d[48]), "+f"(d[49]), "+f"(d[50]), "+f"(d[51]), "+f"(d[52]), "+f"(d[53]), "+f"(d[54]), "+f"(d[55]), "+f"(d[56]), "+f"(d[57]), "+f"(d[58]), "+f"(d[59]), "+f"(d[60]), "+f"(d[61]), "+f"(d[62]), "+f"(d[63])
    : "l"(da), "l"(db), "r"(sc));
}

__device__ __forceinline__ void wgmma_ss_n64_tatb(float (&d)[32], uint64_t da, uint64_t db, int sc) {
  asm volatile("{\n.reg .pred p;\nsetp.ne.b32 p, %34, 0;\n"
    "wgmma.mma_async.sync.aligned.m64n64k16.f32.bf16.bf16 {%0, %1, %2, %3, %4, %5, %6, %7, %8, %9, %10, %11, %12, %13, %14, %15, %16, %17, %18, %19, %20, %21, %22, %23, %24, %25, %26, %27, %28, %29, %30, %31}, %32, %33, p, 1, 1, 1, 1;\n}\n"
    : "+f"(d[0]), "+f"(d[1]), "+f"(d[2]), "+f"(d[3]), "+f"(d[4]), "+f"(d[5]), "+f"(d[6]), "+f"(d[7]), "+f"(d[8]), "+f"(d[9]), "+f"(d[10]), "+f"(d[11]), "+f"(d[12]), "+f"(d[13]), "+f"(d[14]), "+f"(d[15]), "+f"(d[16]), "+f"(d[17]), "+f"(d[18]), "+f"(d[19]), "+f"(d[20]), "+f"(d[21]), "+f"(d[22]), "+f"(d[23]), "+f"(d[24]), "+f"(d[25]), "+f"(d[26]), "+f"(d[27]), "+f"(d[28]), "+f"(d[29]), "+f"(d[30]), "+f"(d[31])
    : "l"(da), "l"(db), "r"(sc));
}

__device__ __forceinline__ void wgmma_ss_n8_tatb(float (&d)[4], uint64_t da, uint64_t db, int sc) {
  asm volatile("{\n.reg .pred p;\nsetp.ne.b32 p, %6, 0;\n"
    "wgmma.mma_async.sync.aligned.m64n8k16.f32.bf16.bf16 {%0, %1, %2, %3}, %4, %5, p, 1, 1, 1, 1;\n}\n"
    : "+f"(d[0]), "+f"(d[1]), "+f"(d[2]), "+f"(d[3])
    : "l"(da), "l"(db), "r"(sc));
}

__device__ __forceinline__ void wgmma_rs_n40_tb(float (&d)[20], uint32_t a0, uint32_t a1, uint32_t a2, uint32_t a3, uint64_t db, int sc) {
  asm volatile("{\n.reg .pred p;\nsetp.ne.b32 p, %25, 0;\n"
    "wgmma.mma_async.sync.aligned.m64n40k16.f32.bf16.bf16 {%0, %1, %2, %3, %4, %5, %6, %7, %8, %9, %10, %11, %12, %13, %14, %15, %16, %17, %18, %19}, {%20, %21, %22, %23}, %24, p, 1, 1, 1;\n}\n"
    : "+f"(d[0]), "+f"(d[1]), "+f"(d[2]), "+f"(d[3]), "+f"(d[4]), "+f"(d[5]), "+f"(d[6]), "+f"(d[7]), "+f"(d[8]), "+f"(d[9]), "+f"(d[10]), "+f"(d[11]), "+f"(d[12]), "+f"(d[13]), "+f"(d[14]), "+f"(d[15]), "+f"(d[16]), "+f"(d[17]), "+f"(d[18]), "+f"(d[19])
    : "r"(a0), "r"(a1), "r"(a2), "r"(a3), "l"(db), "r"(sc));
}


namespace k1 {
constexpr int BM = 256, BN = 192, BK = 64, ST = 4;
constexpr int A_BYTES = BM * BK * 2, B_BYTES = BK * BN * 2, STAGE = A_BYTES + B_BYTES;
constexpr int SMEM = ST * STAGE + 1024 + 256;
constexpr int OFF_PK = 0, OFF_V = 32768, OFF_ONES = 65536, OFF_KV = 69632, OFF_O = 81920;
}

__global__ void __cluster_dims__(2, 1, 1) __launch_bounds__(384, 1)
k1_qkv_attn(const __grid_constant__ CUtensorMap tmx, const __grid_constant__ CUtensorMap tmw) {
  using namespace k1;
  extern __shared__ uint8_t smem_raw[];
  const uint32_t sbase = (smem_u32(smem_raw) + 1023) & ~1023u;
  uint8_t* sgen = smem_raw + (sbase - smem_u32(smem_raw));
  const uint32_t bars = sbase + ST * STAGE;
  const int tid = threadIdx.x, warp = tid >> 5, lane = tid & 31;
  const uint32_t rank = cluster_ctarank();
  const int cl = blockIdx.x >> 1;
  const int mt = cl >> 3;
  const int hp = ((cl & 7) << 1) + rank;
  const int m0 = mt * BM;

  if (tid == 0) {
    for (int s = 0; s < ST; s++) {
      mbar_init(bars + 8 * s, 1);
      mbar_init(bars + 8 * (ST + s), 16);
    }
    asm volatile("fence.mbarrier_init.release.cluster;" ::: "memory");
  }
  cluster_sync_all();

  if (warp >= 8) {
    asm volatile("setmaxnreg.dec.sync.aligned.u32 40;");
    if (warp == 8 && lane == 0) {
      for (int kb = 0; kb < DM / BK; kb++) {
        const int s = kb % ST;
        mbar_wait(bars + 8 * (ST + s), ((kb / ST) & 1) ^ 1);
        const uint32_t full = bars + 8 * s;
        mbar_expect_tx(full, STAGE);
        const uint32_t sa = sbase + s * STAGE, sb = sa + A_BYTES;
        tma_load_2d_mc(sa + rank * 16384, &tmx, full, kb * BK, m0 + rank * 128, (uint16_t)3);
#pragma unroll
        for (int j = 0; j < 3; j++) tma_load_2d(sb + j * 8192, &tmw, full, j * 1024 + hp * 64, kb * BK);
      }
    }
    cluster_sync_all();
  } else {
    asm volatile("setmaxnreg.inc.sync.aligned.u32 232;");
    const int wg = warp >> 2, w4 = warp & 3, g = lane >> 2, t = lane & 3;
    float acc[2][96];
#pragma unroll
    for (int i = 0; i < 96; i++) { acc[0][i] = 0.f; acc[1][i] = 0.f; }
    for (int kb = 0; kb < DM / BK; kb++) {
      const int s = kb % ST;
      mbar_wait(bars + 8 * s, (kb / ST) & 1);
      const uint32_t sa = sbase + s * STAGE + wg * 16384, sb = sbase + s * STAGE + A_BYTES;
      wg_fence();
#pragma unroll
      for (int ks = 0; ks < 4; ks++) {
        const uint64_t db = make_desc(sb + ks * 2048, 8192, 1024);
#pragma unroll
        for (int mb = 0; mb < 2; mb++) {
          const uint64_t da = make_desc(sa + mb * 8192 + ks * 32, 16, 1024);
          wgmma_ss_n192_tb(acc[mb], da, db, 1);
        }
      }
      wg_commit();
      if (kb > 0) {
        wg_wait<1>();
        const int sp = (kb - 1) % ST;
        if (lane == 0) { mbar_arrive_cluster(bars + 8 * (ST + sp), 0); mbar_arrive_cluster(bars + 8 * (ST + sp), 1); }
      }
    }
    wg_wait<0>();
    fence_regs(acc[0]); fence_regs(acc[1]);
    named_bar_sync(1, 256);

#pragma unroll
    for (int mb = 0; mb < 2; mb++) {
#pragma unroll
      for (int h = 0; h < 2; h++) {
        const int r = wg * 128 + mb * 64 + w4 * 16 + g + h * 8;
#pragma unroll
        for (int j = 0; j < 8; j++) {
          const uint32_t off = r * 128 + ((j ^ (r & 7)) << 4) + t * 4;
          const float k0 = acc[mb][4 * (8 + j) + 2 * h], k1v = acc[mb][4 * (8 + j) + 2 * h + 1];
          const float v0 = acc[mb][4 * (16 + j) + 2 * h], v1 = acc[mb][4 * (16 + j) + 2 * h + 1];
          *reinterpret_cast<uint32_t*>(sgen + OFF_PK + off) = pack2(phi_f(k0), phi_f(k1v));
          *reinterpret_cast<uint32_t*>(sgen + OFF_V + off) = pack2(v0, v1);
        }
      }
    }
    if (tid < 256) *reinterpret_cast<uint32_t*>(sgen + OFF_ONES + tid * 4) = 0x3F803F80u;
    fence_async_smem();
    named_bar_sync(1, 256);

    float* part = g_part + (size_t)(hp * 8 + mt) * 2112;
    if (wg == 0) {
      float kv[32], zz[4];
#pragma unroll
      for (int i = 0; i < 32; i++) kv[i] = 0.f;
#pragma unroll
      for (int i = 0; i < 4; i++) zz[i] = 0.f;
      wg_fence();
#pragma unroll
      for (int ks = 0; ks < 16; ks++) {
        const uint64_t da = make_desc(sbase + OFF_PK + ks * 2048, 16, 1024);
        const uint64_t db = make_desc(sbase + OFF_V + ks * 2048, 16, 1024);
        const uint64_t d1 = make_desc(sbase + OFF_ONES, 16, 0);
        wgmma_ss_n64_tatb(kv, da, db, 1);
        wgmma_ss_n8_tatb(zz, da, d1, 1);
      }
      wg_commit();
      wg_wait<0>();
      fence_regs(kv); fence_regs(zz);
      const int hh = w4 >> 1;
#pragma unroll
      for (int h = 0; h < 2; h++) {
        const int d = (w4 & 1) * 16 + g + h * 8;
        float* dst = part + hh * 1056 + d * 32;
#pragma unroll
        for (int j = 0; j < 4; j++) {
          float a0 = hh ? kv[4 * (4 + j) + 2 * h] : kv[4 * j + 2 * h];
          float a1 = hh ? kv[4 * (4 + j) + 2 * h + 1] : kv[4 * j + 2 * h + 1];
          *reinterpret_cast<float2*>(dst + 8 * j + 2 * t) = make_float2(a0, a1);
        }
        if (t == 0) part[hh * 1056 + 1024 + d] = zz[2 * h];
      }
      __threadfence();
      named_bar_sync(2, 128);
      if (tid == 0) atomicAdd(&g_cnt[hp], 1u);
    }
    uint32_t pq[2][4][4];
#pragma unroll
    for (int mb = 0; mb < 2; mb++)
#pragma unroll
      for (int kk = 0; kk < 4; kk++) {
        pq[mb][kk][0] = pack2(phi_f(acc[mb][8 * kk + 0]), phi_f(acc[mb][8 * kk + 1]));
        pq[mb][kk][1] = pack2(phi_f(acc[mb][8 * kk + 2]), phi_f(acc[mb][8 * kk + 3]));
        pq[mb][kk][2] = pack2(phi_f(acc[mb][8 * kk + 4]), phi_f(acc[mb][8 * kk + 5]));
        pq[mb][kk][3] = pack2(phi_f(acc[mb][8 * kk + 6]), phi_f(acc[mb][8 * kk + 7]));
      }
    if (tid == 0) {
      unsigned int v;
      do { asm volatile("ld.acquire.gpu.global.u32 %0, [%1];" : "=r"(v) : "l"(&g_cnt[hp]) : "memory"); } while (v < 8u);
    }
    named_bar_sync(1, 256);
    {
      const float* pb = g_part + (size_t)(hp * 8) * 2112;
      for (int i = tid; i < 528; i += 256) {
        float4 s4 = make_float4(0.f, 0.f, 0.f, 0.f);
#pragma unroll
        for (int p = 0; p < 8; p++) {
          float4 v4 = __ldcg(reinterpret_cast<const float4*>(pb + p * 2112) + i);
          s4.x += v4.x; s4.y += v4.y; s4.z += v4.z; s4.w += v4.w;
        }
        const int hh = i / 264, rem = i - hh * 264;
        uint8_t* tile = sgen + OFF_KV + hh * 4096;
        if (rem < 256) {
          const int d = rem >> 3, e = (rem & 7) * 4;
          const uint32_t off = d * 128 + (((e >> 3) ^ (d & 7)) << 4) + (e & 7) * 2;
          *reinterpret_cast<uint2*>(tile + off) = make_uint2(pack2(s4.x, s4.y), pack2(s4.z, s4.w));
        } else {
          const int d0 = (rem - 256) * 4;
          float zv[4] = {s4.x, s4.y, s4.z, s4.w};
#pragma unroll
          for (int q = 0; q < 4; q++) {
            const int d = d0 + q;
            const uint32_t off = d * 128 + ((4 ^ (d & 7)) << 4);
            *reinterpret_cast<uint4*>(tile + off) = make_uint4(pack2(zv[q], 0.f), 0u, 0u, 0u);
          }
        }
      }
    }
    fence_async_smem();
    named_bar_sync(1, 256);
#pragma unroll
    for (int mb = 0; mb < 2; mb++) {
#pragma unroll
      for (int hh = 0; hh < 2; hh++) {
        float num[20];
#pragma unroll
        for (int i = 0; i < 20; i++) num[i] = 0.f;
        wg_fence();
#pragma unroll
        for (int kk = 0; kk < 2; kk++) {
          const uint64_t db = make_desc(sbase + OFF_KV + hh * 4096 + kk * 2048, 16, 1024);
          wgmma_rs_n40_tb(num, pq[mb][hh * 2 + kk][0], pq[mb][hh * 2 + kk][1], pq[mb][hh * 2 + kk][2], pq[mb][hh * 2 + kk][3], db, 1);
        }
        wg_commit();
        wg_wait<0>();
        fence_regs(num);
#pragma unroll
        for (int h = 0; h < 2; h++) {
          float den = __shfl_sync(0xffffffffu, num[16 + 2 * h], lane & ~3);
          den = bfr(bfr(den) + 1e-6f);
          const int r = wg * 128 + mb * 64 + w4 * 16 + g + h * 8;
#pragma unroll
          for (int j = 0; j < 4; j++) {
            const float o0 = bfr(num[4 * j + 2 * h]) / den, o1 = bfr(num[4 * j + 2 * h + 1]) / den;
            const uint32_t off = r * 128 + (((hh * 4 + j) ^ (r & 7)) << 4) + t * 4;
            *reinterpret_cast<uint32_t*>(sgen + OFF_O + off) = pack2(o0, o1);
          }
        }
      }
    }
    named_bar_sync(1, 256);
    for (int i = tid; i < 256 * 8; i += 256) {
      const int r = i >> 3, c = i & 7;
      uint4 v = *reinterpret_cast<const uint4*>(sgen + OFF_O + r * 128 + ((c ^ (r & 7)) << 4));
      *reinterpret_cast<uint4*>(g_o + (size_t)(m0 + r) * DM + hp * 64 + c * 8) = v;
    }
    cluster_sync_all();
  }
}

namespace k3 {
constexpr int BM = 128, BN = 128, BK = 64, ST = 6;
constexpr int A_BYTES = BM * BK * 2, B_BYTES = BK * BN * 2, STAGE = A_BYTES + B_BYTES;
constexpr int SMEM = ST * STAGE + 1024 + 256;
}

__global__ void __cluster_dims__(2, 1, 1) __launch_bounds__(384, 1)
k3_out(const __grid_constant__ CUtensorMap tmo, const __grid_constant__ CUtensorMap tmw, bf16* __restrict__ out) {
  using namespace k3;
  extern __shared__ uint8_t smem_raw[];
  const uint32_t sbase = (smem_u32(smem_raw) + 1023) & ~1023u;
  const uint32_t bars = sbase + ST * STAGE;
  const int tid = threadIdx.x, warp = tid >> 5, lane = tid & 31;
  const uint32_t rank = cluster_ctarank();
  const int cl = blockIdx.x >> 1;
  const int mt = cl >> 2;
  const int nt = ((cl & 3) << 1) + rank;
  const int m0 = mt * BM, n0 = nt * BN;
  if (blockIdx.x == 0 && tid < 16) g_cnt[tid] = 0;

  if (tid == 0) {
    for (int s = 0; s < ST; s++) {
      mbar_init(bars + 8 * s, 1);
      mbar_init(bars + 8 * (ST + s), 16);
    }
    asm volatile("fence.mbarrier_init.release.cluster;" ::: "memory");
  }
  cluster_sync_all();

  if (warp >= 8) {
    asm volatile("setmaxnreg.dec.sync.aligned.u32 40;");
    if (warp == 8 && lane == 0) {
      for (int kb = 0; kb < DM / BK; kb++) {
        const int s = kb % ST;
        mbar_wait(bars + 8 * (ST + s), ((kb / ST) & 1) ^ 1);
        const uint32_t full = bars + 8 * s;
        mbar_expect_tx(full, STAGE);
        const uint32_t sa = sbase + s * STAGE, sb = sa + A_BYTES;
        tma_load_2d_mc(sa + rank * 8192, &tmo, full, kb * BK, m0 + rank * 64, (uint16_t)3);
#pragma unroll
        for (int j = 0; j < 2; j++) tma_load_2d(sb + j * 8192, &tmw, full, n0 + j * 64, kb * BK);
      }
    }
    cluster_sync_all();
  } else {
    asm volatile("setmaxnreg.inc.sync.aligned.u32 232;");
    const int wg = warp >> 2, w4 = warp & 3, g = lane >> 2, t = lane & 3;
    float acc[64];
#pragma unroll
    for (int i = 0; i < 64; i++) acc[i] = 0.f;
    for (int kb = 0; kb < DM / BK; kb++) {
      const int s = kb % ST;
      mbar_wait(bars + 8 * s, (kb / ST) & 1);
      const uint32_t sa = sbase + s * STAGE + wg * 8192, sb = sbase + s * STAGE + A_BYTES;
      wg_fence();
#pragma unroll
      for (int ks = 0; ks < 4; ks++) {
        const uint64_t db = make_desc(sb + ks * 2048, 8192, 1024);
        const uint64_t da = make_desc(sa + ks * 32, 16, 1024);
        wgmma_ss_n128_tb(acc, da, db, 1);
      }
      wg_commit();
      if (kb > 0) {
        wg_wait<1>();
        const int sp = (kb - 1) % ST;
        if (lane == 0) { mbar_arrive_cluster(bars + 8 * (ST + sp), 0); mbar_arrive_cluster(bars + 8 * (ST + sp), 1); }
      }
    }
    wg_wait<0>();
    fence_regs(acc);
#pragma unroll
    for (int h = 0; h < 2; h++) {
      const int r = m0 + wg * 64 + w4 * 16 + g + h * 8;
      const float gt = g_gate[r];
      const float omg = bfr(1.0f - gt);
#pragma unroll
      for (int j = 0; j < 16; j++) {
        const int c = n0 + 8 * j + 2 * t;
        const __nv_bfloat162 bb = *reinterpret_cast<const __nv_bfloat162*>(g_b + (size_t)r * DM + c);
        const float o0 = bfr(gt * bfr(acc[4 * j + 2 * h])) + bfr(omg * __bfloat162float(bb.x));
        const float o1 = bfr(gt * bfr(acc[4 * j + 2 * h + 1])) + bfr(omg * __bfloat162float(bb.y));
        *reinterpret_cast<uint32_t*>(out + (size_t)r * DM + c) = pack2(o0, o1);
      }
    }
    cluster_sync_all();
  }
}

namespace k2 {
constexpr int CH = 8;
constexpr int UPAD = 128;
constexpr int USZ = UPAD + SEQ;
constexpr int KOFF = 2048 + 16;
constexpr int KSZ = 2112;
constexpr int KCH = 2 * KSZ + 16;
constexpr int OFF_U = 0;
constexpr int OFF_K = OFF_U + CH * USZ * 2;
constexpr int OFF_KQ = OFF_K + CH * KCH * 2;
constexpr int SMEM = OFF_KQ + CH * 648 * 4;
}

__device__ __forceinline__ void mma_bf16(float (&d)[4], uint32_t a0, uint32_t a1, uint32_t a2, uint32_t a3, uint32_t b0, uint32_t b1) {
  asm volatile("mma.sync.aligned.m16n8k16.row.col.f32.bf16.bf16.f32 {%0,%1,%2,%3}, {%4,%5,%6,%7}, {%8,%9}, {%0,%1,%2,%3};"
               : "+f"(d[0]), "+f"(d[1]), "+f"(d[2]), "+f"(d[3]) : "r"(a0), "r"(a1), "r"(a2), "r"(a3), "r"(b0), "r"(b1));
}
__device__ __forceinline__ void mma_tf32(float (&d)[4], uint32_t a0, uint32_t a1, uint32_t a2, uint32_t a3, uint32_t b0, uint32_t b1) {
  asm volatile("mma.sync.aligned.m16n8k8.row.col.f32.tf32.tf32.f32 {%0,%1,%2,%3}, {%4,%5,%6,%7}, {%8,%9}, {%0,%1,%2,%3};"
               : "+f"(d[0]), "+f"(d[1]), "+f"(d[2]), "+f"(d[3]) : "r"(a0), "r"(a1), "r"(a2), "r"(a3), "r"(b0), "r"(b1));
}
__device__ __forceinline__ uint32_t tf32r(float x) { uint32_t r; asm("cvt.rna.tf32.f32 %0, %1;" : "=r"(r) : "f"(x)); return r; }
struct cf { float r, i; };
__device__ __forceinline__ cf cmul(cf a, cf b) { cf c; c.r = a.r * b.r - a.i * b.i; c.i = a.r * b.i + a.i * b.r; return c; }
__device__ __forceinline__ cf csq(cf a) { cf c; c.r = a.r * a.r - a.i * a.i; c.i = 2.f * a.r * a.i; return c; }
__device__ __forceinline__ cf cexpp(float ar, float ai, float p) {
  float e = expf(ar * p), s, c;
  sincosf(ai * p, &s, &c);
  cf w; w.r = e * c; w.i = e * s; return w;
}

__global__ void __launch_bounds__(256, 1)
k2_ssm(const bf16* __restrict__ x, const bf16* __restrict__ logAr, const bf16* __restrict__ Aim, const bf16* __restrict__ Cre,
       const bf16* __restrict__ Cim, const bf16* __restrict__ logdt, const bf16* __restrict__ Dskip,
       const bf16* __restrict__ gatew) {
  using namespace k2;
  extern __shared__ __align__(16) uint8_t sm[];
  const int tid = threadIdx.x, warp = tid >> 5, lane = tid & 31, g = lane >> 2, t = lane & 3;
  const int d0 = blockIdx.x * CH;
  bf16* us = reinterpret_cast<bf16*>(sm + OFF_U);
  bf16* ks = reinterpret_cast<bf16*>(sm + OFF_K);
  float* kq = reinterpret_cast<float*>(sm + OFF_KQ);

  for (int rr = 0; rr < 2; rr++) {
    const int r = blockIdx.x * 16 + warp * 2 + rr;
    float s = 0.f;
    for (int c = lane * 8; c < DM; c += 256) {
      uint4 xv = *reinterpret_cast<const uint4*>(x + (size_t)r * DM + c);
      uint4 wv = *reinterpret_cast<const uint4*>(gatew + c);
      const bf16* xp = reinterpret_cast<const bf16*>(&xv);
      const bf16* wp = reinterpret_cast<const bf16*>(&wv);
#pragma unroll
      for (int q = 0; q < 8; q++) s += bfr(__bfloat162float(xp[q]) * __bfloat162float(wp[q]));
    }
#pragma unroll
    for (int o = 16; o; o >>= 1) s += __shfl_xor_sync(0xffffffffu, s, o);
    if (lane == 0) { float z = bfr(s); g_gate[r] = bfr(1.0f / (1.0f + expf(-z))); }
  }

  for (int i = tid; i < CH * UPAD / 2; i += 256) {
    const int c = i / (UPAD / 2), o = i % (UPAD / 2);
    reinterpret_cast<uint32_t*>(us + c * USZ)[o] = 0u;
  }
  for (int l = tid; l < SEQ; l += 256) {
    uint4 v = *reinterpret_cast<const uint4*>(x + (size_t)l * DM + d0);
    const bf16* p = reinterpret_cast<const bf16*>(&v);
    const int e = l & 15;
    const int pe = ((e & 7) >> 1) * 4 + (e >> 3) * 2 + (e & 1);
    const int pos = UPAD + (l & ~15) + pe;
#pragma unroll
    for (int c = 0; c < CH; c++) us[c * USZ + pos] = p[c];
  }

  {
    const int d = d0 + warp;
    const float dt = bfr(expf(__bfloat162float(logdt[d])));
    float acc[5][4];
#pragma unroll
    for (int a = 0; a < 5; a++)
#pragma unroll
      for (int b = 0; b < 4; b++) acc[a][b] = 0.f;
    float last = 0.f;
    for (int n0 = 0; n0 < NMODE; n0 += 4) {
      const int idx = d * NMODE + n0 + t;
      const float ar = -bfr(expf(__bfloat162float(logAr[idx]))) * dt;
      const float ai = __bfloat162float(Aim[idx]) * dt;
      cf C; C.r = __bfloat162float(Cre[idx]) * dt; C.i = __bfloat162float(Cim[idx]) * dt;
      const cf Y1 = cexpp(ar, ai, (float)g);
      const cf Y8 = cexpp(ar, ai, (float)(8 * g));
      const cf W64 = cexpp(ar, ai, 64.f);
      const cf Y2 = csq(Y1), Y4 = csq(Y2);
      const cf Y16 = csq(Y8), Y32 = csq(Y16), Y64 = csq(Y32);
      const cf W128 = csq(W64), W256 = csq(W128), W512 = csq(W256), W1024 = csq(W512);
      const cf X0a = cmul(C, Y8), X0b = cmul(X0a, W64);
      const cf X1a = cmul(X0a, W128), X1b = cmul(X0b, W128);
      const cf X2a = cmul(cmul(C, W256), Y16), X2b = cmul(X2a, W128);
      const cf X3a = cmul(cmul(C, W512), Y32), X3b = cmul(X3a, W256);
      const cf C4 = cmul(C, W1024);
      const cf X4a = cmul(C4, Y64), X4b = cmul(X4a, W512);
      last += C4.r * W1024.r - C4.i * W1024.i;
      const uint32_t y1r = tf32r(Y1.r), y1i = tf32r(Y1.i);
      mma_tf32(acc[0], tf32r(X0a.r), tf32r(X0b.r), tf32r(-X0a.i), tf32r(-X0b.i), y1r, y1i);
      mma_tf32(acc[1], tf32r(X1a.r), tf32r(X1b.r), tf32r(-X1a.i), tf32r(-X1b.i), y1r, y1i);
      mma_tf32(acc[2], tf32r(X2a.r), tf32r(X2b.r), tf32r(-X2a.i), tf32r(-X2b.i), tf32r(Y2.r), tf32r(Y2.i));
      mma_tf32(acc[3], tf32r(X3a.r), tf32r(X3b.r), tf32r(-X3a.i), tf32r(-X3b.i), tf32r(Y4.r), tf32r(Y4.i));
      mma_tf32(acc[4], tf32r(X4a.r), tf32r(X4b.r), tf32r(-X4a.i), tf32r(-X4b.i), tf32r(Y8.r), tf32r(Y8.i));
    }
    float* kqc = kq + warp * 648;
#pragma unroll
    for (int a = 0; a < 5; a++) {
      kqc[128 * a + 8 * g + 2 * t] = 2.f * acc[a][0];
      kqc[128 * a + 8 * g + 2 * t + 1] = 2.f * acc[a][1];
      kqc[128 * a + 8 * (g + 8) + 2 * t] = 2.f * acc[a][2];
      kqc[128 * a + 8 * (g + 8) + 2 * t + 1] = 2.f * acc[a][3];
    }
    last += __shfl_xor_sync(0xffffffffu, last, 1);
    last += __shfl_xor_sync(0xffffffffu, last, 2);
    if (lane == 0) kqc[640] = 2.f * last;
    __syncwarp();
    bf16* kr = ks + warp * KCH;
    bf16* kr2 = kr + KSZ + 16;
    for (int i = lane; i < KSZ; i += 32) {
      const int xk = KOFF - i;
      float v = 0.f;
      if (xk >= 0 && xk < SEQ) {
        const uint32_t pb = __float_as_uint(bfr((float)xk));
        int id;
        if (xk < 256) id = xk;
        else { const int e = (int)(pb >> 23) - 127; const int q = 128 + ((pb >> 16) & 127); id = 256 + (e - 8) * 128 + (q - 128); }
        v = kqc[id];
      }
      const bf16 bv = __float2bfloat16_rn(v);
      kr[i] = bv;
      if (i > 0) kr2[i - 1] = bv;
    }
    if (lane == 0) kr2[KSZ - 1] = __float2bfloat16_rn(0.f);
  }
  __syncthreads();

  float D[16][4];
#pragma unroll
  for (int j = 0; j < 16; j++)
#pragma unroll
    for (int q = 0; q < 4; q++) D[j][q] = 0.f;
  {
    const bf16* uc = us + warp * USZ + UPAD;
    const bf16* kr = ks + warp * KCH;
    const uint32_t* fbase = reinterpret_cast<const uint32_t*>((g & 1) ? (kr + KSZ + 16) : kr) + ((KOFF - g + 2 * t) >> 1);
    for (int r = 0; r < 8; r++) {
      uint32_t B[16][2];
#pragma unroll
      for (int j = 0; j < 16; j++) {
        const uint2 v = *reinterpret_cast<const uint2*>(uc + 16 * (8 * j - r + g) + 4 * t);
        B[j][0] = v.x; B[j][1] = v.y;
      }
      uint32_t fm1 = fbase[-4 * (2 * r - 1)];
#pragma unroll
      for (int k = 0; k < 16; k++) {
        const int dl = 8 * k + r;
        const uint32_t f0 = fbase[-4 * (2 * dl)];
        const uint32_t f1 = fbase[-4 * (2 * dl + 1)];
        if (k > 0) fm1 = fbase[-4 * (2 * dl - 1)];
#pragma unroll
        for (int j = k; j < 16; j++) mma_bf16(D[j], f0, f1, fm1, f0, B[j - k][0], B[j - k][1]);
      }
    }
  }
  __syncthreads();
  {
    bf16* ys = ks + warp * KCH;
#pragma unroll
    for (int j = 0; j < 16; j++) {
#pragma unroll
      for (int q = 0; q < 4; q++) {
        const int a = 8 * j + 2 * t + (q & 1), b = g + (q >> 1) * 8;
        ys[16 * a + b] = __float2bfloat16_rn(D[j][q]);
      }
    }
  }
  __syncthreads();
  {
    float dsk[CH];
#pragma unroll
    for (int c = 0; c < CH; c++) dsk[c] = __bfloat162float(Dskip[d0 + c]);
    for (int l = tid; l < SEQ; l += 256) {
      uint4 v = *reinterpret_cast<const uint4*>(x + (size_t)l * DM + d0);
      const bf16* p = reinterpret_cast<const bf16*>(&v);
      uint32_t o[4];
#pragma unroll
      for (int c = 0; c < CH; c += 2) {
        const float y0 = __bfloat162float(ks[c * KCH + l]), y1 = __bfloat162float(ks[(c + 1) * KCH + l]);
        const float b0 = y0 + bfr(__bfloat162float(p[c]) * dsk[c]);
        const float b1 = y1 + bfr(__bfloat162float(p[c + 1]) * dsk[c + 1]);
        o[c >> 1] = pack2(b0, b1);
      }
      *reinterpret_cast<uint4*>(g_b + (size_t)l * DM + d0) = make_uint4(o[0], o[1], o[2], o[3]);
    }
  }
}

typedef CUresult (*EncodeFn)(CUtensorMap*, CUtensorMapDataType, cuuint32_t, void*, const cuuint64_t*, const cuuint64_t*,
                             const cuuint32_t*, const cuuint32_t*, CUtensorMapInterleave, CUtensorMapSwizzle,
                             CUtensorMapL2promotion, CUtensorMapFloatOOBfill);

static void make_map(EncodeFn enc, CUtensorMap* m, void* ptr, uint64_t inner, uint64_t outer, uint32_t bi, uint32_t bo) {
  cuuint64_t dims[2] = {inner, outer};
  cuuint64_t strides[1] = {inner * 2};
  cuuint32_t box[2] = {bi, bo};
  cuuint32_t es[2] = {1, 1};
  enc(m, CU_TENSOR_MAP_DATA_TYPE_BFLOAT16, 2, ptr, dims, strides, box, es, CU_TENSOR_MAP_INTERLEAVE_NONE,
      CU_TENSOR_MAP_SWIZZLE_128B, CU_TENSOR_MAP_L2_PROMOTION_L2_256B, CU_TENSOR_MAP_FLOAT_OOB_FILL_NONE);
}

extern "C" void kernel_launch(void* const* d_in, const int* in_sizes, int n_in, void* d_out, int out_size) {
  const bf16* x = (const bf16*)d_in[0];
  const bf16* wqkv = (const bf16*)d_in[1];
  const bf16* wo = (const bf16*)d_in[2];
  const bf16* logAr = (const bf16*)d_in[4];
  const bf16* Aim = (const bf16*)d_in[5];
  const bf16* Cre = (const bf16*)d_in[6];
  const bf16* Cim = (const bf16*)d_in[7];
  const bf16* logdt = (const bf16*)d_in[8];
  const bf16* Dskip = (const bf16*)d_in[9];
  const bf16* gatew = (const bf16*)d_in[10];

  static EncodeFn enc = nullptr;
  static void* p_o = nullptr;
  if (!enc) {
    void* fn = nullptr;
    cudaDriverEntryPointQueryResult qr;
    cudaGetDriverEntryPoint("cuTensorMapEncodeTiled", &fn, cudaEnableDefault, &qr);
    enc = (EncodeFn)fn;
    cudaGetSymbolAddress(&p_o, g_o);
    cudaFuncSetAttribute(k1_qkv_attn, cudaFuncAttributeMaxDynamicSharedMemorySize, k1::SMEM);
    cudaFuncSetAttribute(k2_ssm, cudaFuncAttributeMaxDynamicSharedMemorySize, k2::SMEM);
    cudaFuncSetAttribute(k3_out, cudaFuncAttributeMaxDynamicSharedMemorySize, k3::SMEM);
  }
  CUtensorMap tmx, tmw, tmo, tmwo;
  make_map(enc, &tmx, (void*)x, 1024, 2048, 64, 128);
  make_map(enc, &tmw, (void*)wqkv, 3072, 1024, 64, 64);
  make_map(enc, &tmo, p_o, 1024, 2048, 64, 64);
  make_map(enc, &tmwo, (void*)wo, 1024, 1024, 64, 64);

  k2_ssm<<<128, 256, k2::SMEM>>>(x, logAr, Aim, Cre, Cim, logdt, Dskip, gatew);
  k1_qkv_attn<<<128, 384, k1::SMEM>>>(tmx, tmw);
  k3_out<<<128, 384, k3::SMEM>>>(tmo, tmwo, (bf16*)d_out);
}
```

```cpp
#include <cuda_runtime.h>
#include <cuda_bf16.h>
#include <cuda.h>
#include <stdint.h>

typedef __nv_bfloat16 bf16;

constexpr int SEQ = 2048, DM = 1024, NMODE = 128;

__device__ __align__(1024) bf16 g_o[SEQ * DM];
__device__ __align__(1024) bf16 g_b[SEQ * DM];
__device__ float g_gate[SEQ];
__device__ __align__(16) float g_part[16 * 8 * 2 * 1056];
__device__ unsigned int g_cnt[16];

__device__ __forceinline__ uint32_t smem_u32(const void* p) { return (uint32_t)__cvta_generic_to_shared(p); }
__device__ __forceinline__ void mbar_init(uint32_t bar, uint32_t cnt) {
  asm volatile("mbarrier.init.shared::cta.b64 [%0], %1;" ::"r"(bar), "r"(cnt));
}
__device__ __forceinline__ void mbar_expect_tx(uint32_t bar, uint32_t bytes) {
  asm volatile("mbarrier.arrive.expect_tx.shared::cta.b64 _, [%0], %1;" ::"r"(bar), "r"(bytes) : "memory");
}
__device__ __forceinline__ void mbar_arrive_cluster(uint32_t bar, uint32_t cta) {
  asm volatile(
      "{\n.reg .b32 ra;\nmapa.shared::cluster.u32 ra, %0, %1;\n"
      "mbarrier.arrive.shared::cluster.b64 _, [ra];\n}\n" ::"r"(bar), "r"(cta) : "memory");
}
__device__ __forceinline__ bool mbar_try_wait(uint32_t bar, uint32_t parity) {
  uint32_t ok;
  asm volatile(
      "{\n.reg .pred p;\nmbarrier.try_wait.parity.shared::cta.b64 p, [%1], %2;\nselp.u32 %0, 1, 0, p;\n}\n"
      : "=r"(ok) : "r"(bar), "r"(parity) : "memory");
  return ok;
}
__device__ __forceinline__ void mbar_wait(uint32_t bar, uint32_t parity) {
  while (!mbar_try_wait(bar, parity)) {}
}
__device__ __forceinline__ void tma_load_2d(uint32_t dst, const CUtensorMap* map, uint32_t bar, int c0, int c1) {
  asm volatile(
      "cp.async.bulk.tensor.2d.shared::cluster.global.mbarrier::complete_tx::bytes [%0], [%1, {%3, %4}], [%2];" ::"r"(dst),
      "l"(map), "r"(bar), "r"(c0), "r"(c1) : "memory");
}
__device__ __forceinline__ void tma_load_2d_mc(uint32_t dst, const CUtensorMap* map, uint32_t bar, int c0, int c1,
                                               uint16_t mask) {
  asm volatile(
      "cp.async.bulk.tensor.2d.shared::cluster.global.mbarrier::complete_tx::bytes.multicast::cluster [%0], [%1, {%3, %4}], [%2], %5;" ::"r"(dst),
      "l"(map), "r"(bar), "r"(c0), "r"(c1), "h"(mask) : "memory");
}
__device__ __forceinline__ void cluster_sync_all() {
  asm volatile("barrier.cluster.arrive.release.aligned;\nbarrier.cluster.wait.acquire.aligned;\n" ::: "memory");
}
__device__ __forceinline__ uint32_t cluster_ctarank() {
  uint32_t r; asm volatile("mov.u32 %0, %%cluster_ctarank;" : "=r"(r)); return r;
}
__device__ __forceinline__ void named_bar_sync(int id, int n) { asm volatile("bar.sync %0, %1;" ::"r"(id), "r"(n) : "memory"); }
__device__ __forceinline__ void fence_async_smem() { asm volatile("fence.proxy.async.shared::cta;" ::: "memory"); }
__device__ __forceinline__ void wg_fence() { asm volatile("wgmma.fence.sync.aligned;" ::: "memory"); }
__device__ __forceinline__ void wg_commit() { asm volatile("wgmma.commit_group.sync.aligned;" ::: "memory"); }
template <int N> __device__ __forceinline__ void wg_wait() { asm volatile("wgmma.wait_group.sync.aligned %0;" ::"n"(N) : "memory"); }
__device__ __forceinline__ uint64_t make_desc(uint32_t addr, uint32_t lbo, uint32_t sbo) {
  return (uint64_t)((addr & 0x3FFFF) >> 4) | ((uint64_t)(lbo >> 4) << 16) | ((uint64_t)(sbo >> 4) << 32) | (1ull << 62);
}
__device__ __forceinline__ float bfr(float x) { return __bfloat162float(__float2bfloat16_rn(x)); }
__device__ __forceinline__ uint32_t pack2(float lo, float hi) {
  __nv_bfloat162 v = __floats2bfloat162_rn(lo, hi);
  return *reinterpret_cast<uint32_t*>(&v);
}
__device__ __forceinline__ float phi_f(float acc) {
  float t = bfr(acc);
  float f = t > 0.f ? bfr(t + 1.0f) : bfr(expf(t));
  return bfr(f + 1e-6f);
}
template <int R> __device__ __forceinline__ void fence_regs(float (&d)[R]) {
#pragma unroll
  for (int i = 0; i < R; i++) asm volatile("" : "+f"(d[i])::"memory");
}

__device__ __forceinline__ void wgmma_ss_n192_tb(float (&d)[96], uint64_t da, uint64_t db, int sc) {
  asm volatile("{\n.reg .pred p;\nsetp.ne.b32 p, %98, 0;\n"
    "wgmma.mma_async.sync.aligned.m64n192k16.f32.bf16.bf16 {%0, %1, %2, %3, %4, %5, %6, %7, %8, %9, %10, %11, %12, %13, %14, %15, %16, %17, %18, %19, %20, %21, %22, %23, %24, %25, %26, %27, %28, %29, %30, %31, %32, %33, %34, %35, %36, %37, %38, %39, %40, %41, %42, %43, %44, %45, %46, %47, %48, %49, %50, %51, %52, %53, %54, %55, %56, %57, %58, %59, %60, %61, %62, %63, %64, %65, %66, %67, %68, %69, %70, %71, %72, %73, %74, %75, %76, %77, %78, %79, %80, %81, %82, %83, %84, %85, %86, %87, %88, %89, %90, %91, %92, %93, %94, %95}, %96, %97, p, 1, 1, 0, 1;\n}\n"
    : "+f"(d[0]), "+f"(d[1]), "+f"(d[2]), "+f"(d[3]), "+f"(d[4]), "+f"(d[5]), "+f"(d[6]), "+f"(d[7]), "+f"(d[8]), "+f"(d[9]), "+f"(d[10]), "+f"(d[11]), "+f"(d[12]), "+f"(d[13]), "+f"(d[14]), "+f"(d[15]), "+f"(d[16]), "+f"(d[17]), "+f"(d[18]), "+f"(d[19]), "+f"(d[20]), "+f"(d[21]), "+f"(d[22]), "+f"(d[23]), "+f"(d[24]), "+f"(d[25]), "+f"(d[26]), "+f"(d[27]), "+f"(d[28]), "+f"(d[29]), "+f"(d[30]), "+f"(d[31]), "+f"(d[32]), "+f"(d[33]), "+f"(d[34]), "+f"(d[35]), "+f"(d[36]), "+f"(d[37]), "+f"(d[38]), "+f"(d[39]), "+f"(d[40]), "+f"(d[41]), "+f"(d[42]), "+f"(d[43]), "+f"(d[44]), "+f"(d[45]), "+f"(d[46]), "+f"(d[47]), "+f"(d[48]), "+f"(d[49]), "+f"(d[50]), "+f"(d[51]), "+f"(d[52]), "+f"(d[53]), "+f"(d[54]), "+f"(d[55]), "+f"(d[56]), "+f"(d[57]), "+f"(d[58]), "+f"(d[59]), "+f"(d[60]), "+f"(d[61]), "+f"(d[62]), "+f"(d[63]), "+f"(d[64]), "+f"(d[65]), "+f"(d[66]), "+f"(d[67]), "+f"(d[68]), "+f"(d[69]), "+f"(d[70]), "+f"(d[71]), "+f"(d[72]), "+f"(d[73]), "+f"(d[74]), "+f"(d[75]), "+f"(d[76]), "+f"(d[77]), "+f"(d[78]), "+f"(d[79]), "+f"(d[80]), "+f"(d[81]), "+f"(d[82]), "+f"(d[83]), "+f"(d[84]), "+f"(d[85]), "+f"(d[86]), "+f"(d[87]), "+f"(d[88]), "+f"(d[89]), "+f"(d[90]), "+f"(d[91]), "+f"(d[92]), "+f"(d[93]), "+f"(d[94]), "+f"(d[95])
    : "l"(da), "l"(db), "r"(sc));
}

__device__ __forceinline__ void wgmma_ss_n128_tb(float (&d)[64], uint64_t da, uint64_t db, int sc) {
  asm volatile("{\n.reg .pred p;\nsetp.ne.b32 p, %66, 0;\n"
    "wgmma.mma_async.sync.aligned.m64n128k16.f32.bf16.bf16 {%0, %1, %2, %3, %4, %5, %6, %7, %8, %9, %10, %11, %12, %13, %14, %15, %16, %17, %18, %19, %20, %21, %22, %23, %24, %25, %26, %27, %28, %29, %30, %31, %32, %33, %34, %35, %36, %37, %38, %39, %40, %41, %42, %43, %44, %45, %46, %47, %48, %49, %50, %51, %52, %53, %54, %55, %56, %57, %58, %59, %60, %61, %62, %63}, %64, %65, p, 1, 1, 0, 1;\n}\n"
    : "+f"(d[0]), "+f"(d[1]), "+f"(d[2]), "+f"(d[3]), "+f"(d[4]), "+f"(d[5]), "+f"(d[6]), "+f"(d[7]), "+f"(d[8]), "+f"(d[9]), "+f"(d[10]), "+f"(d[11]), "+f"(d[12]), "+f"(d[13]), "+f"(d[14]), "+f"(d[15]), "+f"(d[16]), "+f"(d[17]), "+f"(d[18]), "+f"(d[19]), "+f"(d[20]), "+f"(d[21]), "+f"(d[22]), "+f"(d[23]), "+f"(d[24]), "+f"(d[25]), "+f"(d[26]), "+f"(d[27]), "+f"(d[28]), "+f"(d[29]), "+f"(d[30]), "+f"(d[31]), "+f"(d[32]), "+f"(d[33]), "+f"(d[34]), "+f"(d[35]), "+f"(d[36]), "+f"(d[37]), "+f"(d[38]), "+f"(d[39]), "+f"(d[40]), "+f"(d[41]), "+f"(d[42]), "+f"(d[43]), "+f"(d[44]), "+f"(d[45]), "+f"(d[46]), "+f"(d[47]), "+f"(d[48]), "+f"(d[49]), "+f"(d[50]), "+f"(d[51]), "+f"(d[52]), "+f"(d[53]), "+f"(d[54]), "+f"(d[55]), "+f"(d[56]), "+f"(d[57]), "+f"(d[58]), "+f"(d[59]), "+f"(d[60]), "+f"(d[61]), "+f"(d[62]), "+f"(d[63])
    : "l"(da), "l"(db), "r"(sc));
}

__device__ __forceinline__ void wgmma_ss_n64_tatb(float (&d)[32], uint64_t da, uint64_t db, int sc) {
  asm volatile("{\n.reg .pred p;\nsetp.ne.b32 p, %34, 0;\n"
    "wgmma.mma_async.sync.aligned.m64n64k16.f32.bf16.bf16 {%0, %1, %2, %3, %4, %5, %6, %7, %8, %9, %10, %11, %12, %13, %14, %15, %16, %17, %18, %19, %20, %21, %22, %23, %24, %25, %26, %27, %28, %29, %30, %31}, %32, %33, p, 1, 1, 1, 1;\n}\n"
    : "+f"(d[0]), "+f"(d[1]), "+f"(d[2]), "+f"(d[3]), "+f"(d[4]), "+f"(d[5]), "+f"(d[6]), "+f"(d[7]), "+f"(d[8]), "+f"(d[9]), "+f"(d[10]), "+f"(d[11]), "+f"(d[12]), "+f"(d[13]), "+f"(d[14]), "+f"(d[15]), "+f"(d[16]), "+f"(d[17]), "+f"(d[18]), "+f"(d[19]), "+f"(d[20]), "+f"(d[21]), "+f"(d[22]), "+f"(d[23]), "+f"(d[24]), "+f"(d[25]), "+f"(d[26]), "+f"(d[27]), "+f"(d[28]), "+f"(d[29]), "+f"(d[30]), "+f"(d[31])
    : "l"(da), "l"(db), "r"(sc));
}

__device__ __forceinline__ void wgmma_ss_n8_tatb(float (&d)[4], uint64_t da, uint64_t db, int sc) {
  asm volatile("{\n.reg .pred p;\nsetp.ne.b32 p, %6, 0;\n"
    "wgmma.mma_async.sync.aligned.m64n8k16.f32.bf16.bf16 {%0, %1, %2, %3}, %4, %5, p, 1, 1, 1, 1;\n}\n"
    : "+f"(d[0]), "+f"(d[1]), "+f"(d[2]), "+f"(d[3])
    : "l"(da), "l"(db), "r"(sc));
}

__device__ __forceinline__ void wgmma_rs_n40_tb(float (&d)[20], uint32_t a0, uint32_t a1, uint32_t a2, uint32_t a3, uint64_t db, int sc) {
  asm volatile("{\n.reg .pred p;\nsetp.ne.b32 p, %25, 0;\n"
    "wgmma.mma_async.sync.aligned.m64n40k16.f32.bf16.bf16 {%0, %1, %2, %3, %4, %5, %6, %7, %8, %9, %10, %11, %12, %13, %14, %15, %16, %17, %18, %19}, {%20, %21, %22, %23}, %24, p, 1, 1, 1;\n}\n"
    : "+f"(d[0]), "+f"(d[1]), "+f"(d[2]), "+f"(d[3]), "+f"(d[4]), "+f"(d[5]), "+f"(d[6]), "+f"(d[7]), "+f"(d[8]), "+f"(d[9]), "+f"(d[10]), "+f"(d[11]), "+f"(d[12]), "+f"(d[13]), "+f"(d[14]), "+f"(d[15]), "+f"(d[16]), "+f"(d[17]), "+f"(d[18]), "+f"(d[19])
    : "r"(a0), "r"(a1), "r"(a2), "r"(a3), "l"(db), "r"(sc));
}


namespace k1 {
constexpr int BM = 256, BN = 192, BK = 64, ST = 4;
constexpr int A_BYTES = BM * BK * 2, B_BYTES = BK * BN * 2, STAGE = A_BYTES + B_BYTES;
constexpr int SMEM = ST * STAGE + 1024 + 256;
constexpr int OFF_PK = 0, OFF_V = 32768, OFF_ONES = 65536, OFF_KV = 69632, OFF_O = 81920, OFF_RED = 114688;
}

__global__ void __cluster_dims__(2, 1, 1) __launch_bounds__(384, 1)
k1_qkv_attn(const __grid_constant__ CUtensorMap tmx, const __grid_constant__ CUtensorMap tmw) {
  using namespace k1;
  extern __shared__ uint8_t smem_raw[];
  const uint32_t sbase = (smem_u32(smem_raw) + 1023) & ~1023u;
  uint8_t* sgen = smem_raw + (sbase - smem_u32(smem_raw));
  const uint32_t bars = sbase + ST * STAGE;
  const int tid = threadIdx.x, warp = tid >> 5, lane = tid & 31;
  const uint32_t rank = cluster_ctarank();
  const int cl = blockIdx.x >> 1;
  const int mt = cl >> 3;
  const int hp = ((cl & 7) << 1) + rank;
  const int m0 = mt * BM;

  if (tid == 0) {
    for (int s = 0; s < ST; s++) {
      mbar_init(bars + 8 * s, 1);
      mbar_init(bars + 8 * (ST + s), 16);
    }
    asm volatile("fence.mbarrier_init.release.cluster;" ::: "memory");
  }
  cluster_sync_all();

  if (warp >= 8) {
    asm volatile("setmaxnreg.dec.sync.aligned.u32 40;");
    if (warp == 8 && lane == 0) {
      for (int kb = 0; kb < DM / BK; kb++) {
        const int s = kb % ST;
        mbar_wait(bars + 8 * (ST + s), ((kb / ST) & 1) ^ 1);
        const uint32_t full = bars + 8 * s;
        mbar_expect_tx(full, STAGE);
        const uint32_t sa = sbase + s * STAGE, sb = sa + A_BYTES;
        tma_load_2d_mc(sa + rank * 16384, &tmx, full, kb * BK, m0 + rank * 128, (uint16_t)3);
#pragma unroll
        for (int j = 0; j < 3; j++) tma_load_2d(sb + j * 8192, &tmw, full, j * 1024 + hp * 64, kb * BK);
      }
    }
    cluster_sync_all();
  } else {
    asm volatile("setmaxnreg.inc.sync.aligned.u32 232;");
    const int wg = warp >> 2, w4 = warp & 3, g = lane >> 2, t = lane & 3;
    float acc[2][96];
#pragma unroll
    for (int i = 0; i < 96; i++) { acc[0][i] = 0.f; acc[1][i] = 0.f; }
    for (int kb = 0; kb < DM / BK; kb++) {
      const int s = kb % ST;
      mbar_wait(bars + 8 * s, (kb / ST) & 1);
      const uint32_t sa = sbase + s * STAGE + wg * 16384, sb = sbase + s * STAGE + A_BYTES;
      wg_fence();
#pragma unroll
      for (int ks = 0; ks < 4; ks++) {
        const uint64_t db = make_desc(sb + ks * 2048, 8192, 1024);
#pragma unroll
        for (int mb = 0; mb < 2; mb++) {
          const uint64_t da = make_desc(sa + mb * 8192 + ks * 32, 16, 1024);
          wgmma_ss_n192_tb(acc[mb], da, db, 1);
        }
      }
      wg_commit();
      if (kb > 0) {
        wg_wait<1>();
        const int sp = (kb - 1) % ST;
        if (lane == 0) { mbar_arrive_cluster(bars + 8 * (ST + sp), 0); mbar_arrive_cluster(bars + 8 * (ST + sp), 1); }
      }
    }
    wg_wait<0>();
    fence_regs(acc[0]); fence_regs(acc[1]);
    named_bar_sync(1, 256);

#pragma unroll
    for (int mb = 0; mb < 2; mb++) {
#pragma unroll
      for (int h = 0; h < 2; h++) {
        const int r = wg * 128 + mb * 64 + w4 * 16 + g + h * 8;
#pragma unroll
        for (int j = 0; j < 8; j++) {
          const uint32_t off = r * 128 + ((j ^ (r & 7)) << 4) + t * 4;
          const float k0 = acc[mb][4 * (8 + j) + 2 * h], k1v = acc[mb][4 * (8 + j) + 2 * h + 1];
          const float v0 = acc[mb][4 * (16 + j) + 2 * h], v1 = acc[mb][4 * (16 + j) + 2 * h + 1];
          *reinterpret_cast<uint32_t*>(sgen + OFF_PK + off) = pack2(phi_f(k0), phi_f(k1v));
          *reinterpret_cast<uint32_t*>(sgen + OFF_V + off) = pack2(v0, v1);
        }
      }
    }
    if (tid < 256) *reinterpret_cast<uint32_t*>(sgen + OFF_ONES + tid * 4) = 0x3F803F80u;
    fence_async_smem();
    named_bar_sync(1, 256);

    float* part = g_part + (size_t)(hp * 8 + mt) * 2112;
    {
      float kv[32], zz[4];
#pragma unroll
      for (int i = 0; i < 32; i++) kv[i] = 0.f;
#pragma unroll
      for (int i = 0; i < 4; i++) zz[i] = 0.f;
      wg_fence();
#pragma unroll
      for (int ks = 0; ks < 8; ks++) {
        const uint64_t da = make_desc(sbase + OFF_PK + wg * 16384 + ks * 2048, 16, 1024);
        const uint64_t db = make_desc(sbase + OFF_V + wg * 16384 + ks * 2048, 16, 1024);
        const uint64_t d1 = make_desc(sbase + OFF_ONES, 16, 0);
        wgmma_ss_n64_tatb(kv, da, db, 1);
        wgmma_ss_n8_tatb(zz, da, d1, 1);
      }
      wg_commit();
      wg_wait<0>();
      fence_regs(kv); fence_regs(zz);
      const int hh = w4 >> 1;
      float* red = reinterpret_cast<float*>(sgen + OFF_RED);
      float vals[2][4][2];
#pragma unroll
      for (int h = 0; h < 2; h++)
#pragma unroll
        for (int j = 0; j < 4; j++) {
          vals[h][j][0] = hh ? kv[4 * (4 + j) + 2 * h] : kv[4 * j + 2 * h];
          vals[h][j][1] = hh ? kv[4 * (4 + j) + 2 * h + 1] : kv[4 * j + 2 * h + 1];
        }
      if (wg == 1) {
#pragma unroll
        for (int h = 0; h < 2; h++) {
          const int d = (w4 & 1) * 16 + g + h * 8;
#pragma unroll
          for (int j = 0; j < 4; j++)
            *reinterpret_cast<float2*>(red + hh * 1056 + d * 32 + 8 * j + 2 * t) = make_float2(vals[h][j][0], vals[h][j][1]);
          if (t == 0) red[hh * 1056 + 1024 + d] = zz[2 * h];
        }
      }
      named_bar_sync(1, 256);
      if (wg == 0) {
#pragma unroll
        for (int h = 0; h < 2; h++) {
          const int d = (w4 & 1) * 16 + g + h * 8;
#pragma unroll
          for (int j = 0; j < 4; j++) {
            const float2 o = *reinterpret_cast<const float2*>(red + hh * 1056 + d * 32 + 8 * j + 2 * t);
            *reinterpret_cast<float2*>(part + hh * 1056 + d * 32 + 8 * j + 2 * t) = make_float2(vals[h][j][0] + o.x, vals[h][j][1] + o.y);
          }
          if (t == 0) part[hh * 1056 + 1024 + d] = zz[2 * h] + red[hh * 1056 + 1024 + d];
        }
        __threadfence();
        named_bar_sync(2, 128);
        if (tid == 0) atomicAdd(&g_cnt[hp], 1u);
      }
    }
    uint32_t pq[2][4][4];
#pragma unroll
    for (int mb = 0; mb < 2; mb++)
#pragma unroll
      for (int kk = 0; kk < 4; kk++) {
        pq[mb][kk][0] = pack2(phi_f(acc[mb][8 * kk + 0]), phi_f(acc[mb][8 * kk + 1]));
        pq[mb][kk][1] = pack2(phi_f(acc[mb][8 * kk + 2]), phi_f(acc[mb][8 * kk + 3]));
        pq[mb][kk][2] = pack2(phi_f(acc[mb][8 * kk + 4]), phi_f(acc[mb][8 * kk + 5]));
        pq[mb][kk][3] = pack2(phi_f(acc[mb][8 * kk + 6]), phi_f(acc[mb][8 * kk + 7]));
      }
    if (tid == 0) {
      unsigned int v;
      do { asm volatile("ld.acquire.gpu.global.u32 %0, [%1];" : "=r"(v) : "l"(&g_cnt[hp]) : "memory"); } while (v < 8u);
    }
    named_bar_sync(1, 256);
    {
      const float* pb = g_part + (size_t)(hp * 8) * 2112;
      for (int i = tid; i < 528; i += 256) {
        float4 s4 = make_float4(0.f, 0.f, 0.f, 0.f);
#pragma unroll
        for (int p = 0; p < 8; p++) {
          float4 v4 = __ldcg(reinterpret_cast<const float4*>(pb + p * 2112) + i);
          s4.x += v4.x; s4.y += v4.y; s4.z += v4.z; s4.w += v4.w;
        }
        const int hh = i / 264, rem = i - hh * 264;
        uint8_t* tile = sgen + OFF_KV + hh * 4096;
        if (rem < 256) {
          const int d = rem >> 3, e = (rem & 7) * 4;
          const uint32_t off = d * 128 + (((e >> 3) ^ (d & 7)) << 4) + (e & 7) * 2;
          *reinterpret_cast<uint2*>(tile + off) = make_uint2(pack2(s4.x, s4.y), pack2(s4.z, s4.w));
        } else {
          const int d0 = (rem - 256) * 4;
          float zv[4] = {s4.x, s4.y, s4.z, s4.w};
#pragma unroll
          for (int q = 0; q < 4; q++) {
            const int d = d0 + q;
            const uint32_t off = d * 128 + ((4 ^ (d & 7)) << 4);
            *reinterpret_cast<uint4*>(tile + off) = make_uint4(pack2(zv[q], 0.f), 0u, 0u, 0u);
          }
        }
      }
    }
    fence_async_smem();
    named_bar_sync(1, 256);
#pragma unroll
    for (int mb = 0; mb < 2; mb++) {
#pragma unroll
      for (int hh = 0; hh < 2; hh++) {
        float num[20];
#pragma unroll
        for (int i = 0; i < 20; i++) num[i] = 0.f;
        wg_fence();
#pragma unroll
        for (int kk = 0; kk < 2; kk++) {
          const uint64_t db = make_desc(sbase + OFF_KV + hh * 4096 + kk * 2048, 16, 1024);
          wgmma_rs_n40_tb(num, pq[mb][hh * 2 + kk][0], pq[mb][hh * 2 + kk][1], pq[mb][hh * 2 + kk][2], pq[mb][hh * 2 + kk][3], db, 1);
        }
        wg_commit();
        wg_wait<0>();
        fence_regs(num);
#pragma unroll
        for (int h = 0; h < 2; h++) {
          float den = __shfl_sync(0xffffffffu, num[16 + 2 * h], lane & ~3);
          den = bfr(bfr(den) + 1e-6f);
          const int r = wg * 128 + mb * 64 + w4 * 16 + g + h * 8;
#pragma unroll
          for (int j = 0; j < 4; j++) {
            const float o0 = bfr(num[4 * j + 2 * h]) / den, o1 = bfr(num[4 * j + 2 * h + 1]) / den;
            const uint32_t off = r * 128 + (((hh * 4 + j) ^ (r & 7)) << 4) + t * 4;
            *reinterpret_cast<uint32_t*>(sgen + OFF_O + off) = pack2(o0, o1);
          }
        }
      }
    }
    named_bar_sync(1, 256);
    for (int i = tid; i < 256 * 8; i += 256) {
      const int r = i >> 3, c = i & 7;
      uint4 v = *reinterpret_cast<const uint4*>(sgen + OFF_O + r * 128 + ((c ^ (r & 7)) << 4));
      *reinterpret_cast<uint4*>(g_o + (size_t)(m0 + r) * DM + hp * 64 + c * 8) = v;
    }
    cluster_sync_all();
  }
}

namespace k3 {
constexpr int BM = 128, BN = 128, BK = 64, ST = 6;
constexpr int A_BYTES = BM * BK * 2, B_BYTES = BK * BN * 2, STAGE = A_BYTES + B_BYTES;
constexpr int SMEM = ST * STAGE + 1024 + 256;
}

__global__ void __cluster_dims__(2, 1, 1) __launch_bounds__(384, 1)
k3_out(const __grid_constant__ CUtensorMap tmo, const __grid_constant__ CUtensorMap tmw, bf16* __restrict__ out) {
  using namespace k3;
  extern __shared__ uint8_t smem_raw[];
  const uint32_t sbase = (smem_u32(smem_raw) + 1023) & ~1023u;
  const uint32_t bars = sbase + ST * STAGE;
  const int tid = threadIdx.x, warp = tid >> 5, lane = tid & 31;
  const uint32_t rank = cluster_ctarank();
  const int cl = blockIdx.x >> 1;
  const int mt = cl >> 2;
  const int nt = ((cl & 3) << 1) + rank;
  const int m0 = mt * BM, n0 = nt * BN;
  if (blockIdx.x == 0 && tid < 16) g_cnt[tid] = 0;

  if (tid == 0) {
    for (int s = 0; s < ST; s++) {
      mbar_init(bars + 8 * s, 1);
      mbar_init(bars + 8 * (ST + s), 16);
    }
    asm volatile("fence.mbarrier_init.release.cluster;" ::: "memory");
  }
  cluster_sync_all();

  if (warp >= 8) {
    asm volatile("setmaxnreg.dec.sync.aligned.u32 40;");
    if (warp == 8 && lane == 0) {
      for (int kb = 0; kb < DM / BK; kb++) {
        const int s = kb % ST;
        mbar_wait(bars + 8 * (ST + s), ((kb / ST) & 1) ^ 1);
        const uint32_t full = bars + 8 * s;
        mbar_expect_tx(full, STAGE);
        const uint32_t sa = sbase + s * STAGE, sb = sa + A_BYTES;
        tma_load_2d_mc(sa + rank * 8192, &tmo, full, kb * BK, m0 + rank * 64, (uint16_t)3);
#pragma unroll
        for (int j = 0; j < 2; j++) tma_load_2d(sb + j * 8192, &tmw, full, n0 + j * 64, kb * BK);
      }
    }
    cluster_sync_all();
  } else {
    asm volatile("setmaxnreg.inc.sync.aligned.u32 232;");
    const int wg = warp >> 2, w4 = warp & 3, g = lane >> 2, t = lane & 3;
    float acc[64];
#pragma unroll
    for (int i = 0; i < 64; i++) acc[i] = 0.f;
    for (int kb = 0; kb < DM / BK; kb++) {
      const int s = kb % ST;
      mbar_wait(bars + 8 * s, (kb / ST) & 1);
      const uint32_t sa = sbase + s * STAGE + wg * 8192, sb = sbase + s * STAGE + A_BYTES;
      wg_fence();
#pragma unroll
      for (int ks = 0; ks < 4; ks++) {
        const uint64_t db = make_desc(sb + ks * 2048, 8192, 1024);
        const uint64_t da = make_desc(sa + ks * 32, 16, 1024);
        wgmma_ss_n128_tb(acc, da, db, 1);
      }
      wg_commit();
      if (kb > 0) {
        wg_wait<1>();
        const int sp = (kb - 1) % ST;
        if (lane == 0) { mbar_arrive_cluster(bars + 8 * (ST + sp), 0); mbar_arrive_cluster(bars + 8 * (ST + sp), 1); }
      }
    }
    wg_wait<0>();
    fence_regs(acc);
#pragma unroll
    for (int h = 0; h < 2; h++) {
      const int r = m0 + wg * 64 + w4 * 16 + g + h * 8;
      const float gt = g_gate[r];
      const float omg = bfr(1.0f - gt);
#pragma unroll
      for (int j = 0; j < 16; j++) {
        const int c = n0 + 8 * j + 2 * t;
        const __nv_bfloat162 bb = *reinterpret_cast<const __nv_bfloat162*>(g_b + (size_t)r * DM + c);
        const float o0 = bfr(gt * bfr(acc[4 * j + 2 * h])) + bfr(omg * __bfloat162float(bb.x));
        const float o1 = bfr(gt * bfr(acc[4 * j + 2 * h + 1])) + bfr(omg * __bfloat162float(bb.y));
        *reinterpret_cast<uint32_t*>(out + (size_t)r * DM + c) = pack2(o0, o1);
      }
    }
    cluster_sync_all();
  }
}

namespace k2 {
constexpr int CH = 8;
constexpr int UPAD = 128;
constexpr int USZ = UPAD + SEQ;
constexpr int KOFF = 2048 + 16;
constexpr int KSZ = 2112;
constexpr int KCH = 2 * KSZ + 16;
constexpr int OFF_U = 0;
constexpr int OFF_K = OFF_U + CH * USZ * 2;
constexpr int OFF_KQ = OFF_K + CH * KCH * 2;
constexpr int SMEM = OFF_KQ + CH * 648 * 4;
}

__device__ __forceinline__ void mma_bf16(float (&d)[4], uint32_t a0, uint32_t a1, uint32_t a2, uint32_t a3, uint32_t b0, uint32_t b1) {
  asm volatile("mma.sync.aligned.m16n8k16.row.col.f32.bf16.bf16.f32 {%0,%1,%2,%3}, {%4,%5,%6,%7}, {%8,%9}, {%0,%1,%2,%3};"
               : "+f"(d[0]), "+f"(d[1]), "+f"(d[2]), "+f"(d[3]) : "r"(a0), "r"(a1), "r"(a2), "r"(a3), "r"(b0), "r"(b1));
}
__device__ __forceinline__ void mma_tf32(float (&d)[4], uint32_t a0, uint32_t a1, uint32_t a2, uint32_t a3, uint32_t b0, uint32_t b1) {
  asm volatile("mma.sync.aligned.m16n8k8.row.col.f32.tf32.tf32.f32 {%0,%1,%2,%3}, {%4,%5,%6,%7}, {%8,%9}, {%0,%1,%2,%3};"
               : "+f"(d[0]), "+f"(d[1]), "+f"(d[2]), "+f"(d[3]) : "r"(a0), "r"(a1), "r"(a2), "r"(a3), "r"(b0), "r"(b1));
}
__device__ __forceinline__ uint32_t tf32r(float x) { uint32_t r; asm("cvt.rna.tf32.f32 %0, %1;" : "=r"(r) : "f"(x)); return r; }
struct cf { float r, i; };
__device__ __forceinline__ cf cmul(cf a, cf b) { cf c; c.r = a.r * b.r - a.i * b.i; c.i = a.r * b.i + a.i * b.r; return c; }
__device__ __forceinline__ cf csq(cf a) { cf c; c.r = a.r * a.r - a.i * a.i; c.i = 2.f * a.r * a.i; return c; }
__device__ __forceinline__ cf cexpp(float ar, float ai, float p) {
  float e = expf(ar * p), s, c;
  sincosf(ai * p, &s, &c);
  cf w; w.r = e * c; w.i = e * s; return w;
}

__global__ void __launch_bounds__(256, 1)
k2_ssm(const bf16* __restrict__ x, const bf16* __restrict__ logAr, const bf16* __restrict__ Aim, const bf16* __restrict__ Cre,
       const bf16* __restrict__ Cim, const bf16* __restrict__ logdt, const bf16* __restrict__ Dskip,
       const bf16* __restrict__ gatew) {
  using namespace k2;
  extern __shared__ __align__(16) uint8_t sm[];
  const int tid = threadIdx.x, warp = tid >> 5, lane = tid & 31, g = lane >> 2, t = lane & 3;
  const int d0 = blockIdx.x * CH;
  bf16* us = reinterpret_cast<bf16*>(sm + OFF_U);
  bf16* ks = reinterpret_cast<bf16*>(sm + OFF_K);
  float* kq = reinterpret_cast<float*>(sm + OFF_KQ);

  for (int rr = 0; rr < 2; rr++) {
    const int r = blockIdx.x * 16 + warp * 2 + rr;
    float s = 0.f;
    for (int c = lane * 8; c < DM; c += 256) {
      uint4 xv = *reinterpret_cast<const uint4*>(x + (size_t)r * DM + c);
      uint4 wv = *reinterpret_cast<const uint4*>(gatew + c);
      const bf16* xp = reinterpret_cast<const bf16*>(&xv);
      const bf16* wp = reinterpret_cast<const bf16*>(&wv);
#pragma unroll
      for (int q = 0; q < 8; q++) s += bfr(__bfloat162float(xp[q]) * __bfloat162float(wp[q]));
    }
#pragma unroll
    for (int o = 16; o; o >>= 1) s += __shfl_xor_sync(0xffffffffu, s, o);
    if (lane == 0) { float z = bfr(s); g_gate[r] = bfr(1.0f / (1.0f + expf(-z))); }
  }

  for (int i = tid; i < CH * UPAD / 2; i += 256) {
    const int c = i / (UPAD / 2), o = i % (UPAD / 2);
    reinterpret_cast<uint32_t*>(us + c * USZ)[o] = 0u;
  }
  for (int l = tid; l < SEQ; l += 256) {
    uint4 v = *reinterpret_cast<const uint4*>(x + (size_t)l * DM + d0);
    const bf16* p = reinterpret_cast<const bf16*>(&v);
    const int e = l & 15;
    const int pe = ((e & 7) >> 1) * 4 + (e >> 3) * 2 + (e & 1);
    const int pos = UPAD + (l & ~15) + pe;
#pragma unroll
    for (int c = 0; c < CH; c++) us[c * USZ + pos] = p[c];
  }

  {
    const int d = d0 + warp;
    const float dt = bfr(expf(__bfloat162float(logdt[d])));
    float acc[5][4];
#pragma unroll
    for (int a = 0; a < 5; a++)
#pragma unroll
      for (int b = 0; b < 4; b++) acc[a][b] = 0.f;
    float last = 0.f;
    for (int n0 = 0; n0 < NMODE; n0 += 4) {
      const int idx = d * NMODE + n0 + t;
      const float ar = -bfr(expf(__bfloat162float(logAr[idx]))) * dt;
      const float ai = __bfloat162float(Aim[idx]) * dt;
      cf C; C.r = __bfloat162float(Cre[idx]) * dt; C.i = __bfloat162float(Cim[idx]) * dt;
      const cf Y1 = cexpp(ar, ai, (float)g);
      const cf Y8 = cexpp(ar, ai, (float)(8 * g));
      const cf W64 = cexpp(ar, ai, 64.f);
      const cf Y2 = csq(Y1), Y4 = csq(Y2);
      const cf Y16 = csq(Y8), Y32 = csq(Y16), Y64 = csq(Y32);
      const cf W128 = csq(W64), W256 = csq(W128), W512 = csq(W256), W1024 = csq(W512);
      const cf X0a = cmul(C, Y8), X0b = cmul(X0a, W64);
      const cf X1a = cmul(X0a, W128), X1b = cmul(X0b, W128);
      const cf X2a = cmul(cmul(C, W256), Y16), X2b = cmul(X2a, W128);
      const cf X3a = cmul(cmul(C, W512), Y32), X3b = cmul(X3a, W256);
      const cf C4 = cmul(C, W1024);
      const cf X4a = cmul(C4, Y64), X4b = cmul(X4a, W512);
      last += C4.r * W1024.r - C4.i * W1024.i;
      const uint32_t y1r = tf32r(Y1.r), y1i = tf32r(Y1.i);
      mma_tf32(acc[0], tf32r(X0a.r), tf32r(X0b.r), tf32r(-X0a.i), tf32r(-X0b.i), y1r, y1i);
      mma_tf32(acc[1], tf32r(X1a.r), tf32r(X1b.r), tf32r(-X1a.i), tf32r(-X1b.i), y1r, y1i);
      mma_tf32(acc[2], tf32r(X2a.r), tf32r(X2b.r), tf32r(-X2a.i), tf32r(-X2b.i), tf32r(Y2.r), tf32r(Y2.i));
      mma_tf32(acc[3], tf32r(X3a.r), tf32r(X3b.r), tf32r(-X3a.i), tf32r(-X3b.i), tf32r(Y4.r), tf32r(Y4.i));
      mma_tf32(acc[4], tf32r(X4a.r), tf32r(X4b.r), tf32r(-X4a.i), tf32r(-X4b.i), tf32r(Y8.r), tf32r(Y8.i));
    }
    float* kqc = kq + warp * 648;
#pragma unroll
    for (int a = 0; a < 5; a++) {
      kqc[128 * a + 8 * g + 2 * t] = 2.f * acc[a][0];
      kqc[128 * a + 8 * g + 2 * t + 1] = 2.f * acc[a][1];
      kqc[128 * a + 8 * (g + 8) + 2 * t] = 2.f * acc[a][2];
      kqc[128 * a + 8 * (g + 8) + 2 * t + 1] = 2.f * acc[a][3];
    }
    last += __shfl_xor_sync(0xffffffffu, last, 1);
    last += __shfl_xor_sync(0xffffffffu, last, 2);
    if (lane == 0) kqc[640] = 2.f * last;
    __syncwarp();
    bf16* kr = ks + warp * KCH;
    bf16* kr2 = kr + KSZ + 16;
    for (int i = lane; i < KSZ; i += 32) {
      const int xk = KOFF - i;
      float v = 0.f;
      if (xk >= 0 && xk < SEQ) {
        const uint32_t pb = __float_as_uint(bfr((float)xk));
        int id;
        if (xk < 256) id = xk;
        else { const int e = (int)(pb >> 23) - 127; const int q = 128 + ((pb >> 16) & 127); id = 256 + (e - 8) * 128 + (q - 128); }
        v = kqc[id];
      }
      const bf16 bv = __float2bfloat16_rn(v);
      kr[i] = bv;
      if (i > 0) kr2[i - 1] = bv;
    }
    if (lane == 0) kr2[KSZ - 1] = __float2bfloat16_rn(0.f);
  }
  __syncthreads();

  float D[16][4];
#pragma unroll
  for (int j = 0; j < 16; j++)
#pragma unroll
    for (int q = 0; q < 4; q++) D[j][q] = 0.f;
  {
    const bf16* uc = us + warp * USZ + UPAD;
    const bf16* kr = ks + warp * KCH;
    const uint32_t* fbase = reinterpret_cast<const uint32_t*>((g & 1) ? (kr + KSZ + 16) : kr) + ((KOFF - g + 2 * t) >> 1);
    for (int r = 0; r < 8; r++) {
      uint32_t B[16][2];
#pragma unroll
      for (int j = 0; j < 16; j++) {
        const uint2 v = *reinterpret_cast<const uint2*>(uc + 16 * (8 * j - r + g) + 4 * t);
        B[j][0] = v.x; B[j][1] = v.y;
      }
      uint32_t fm1 = fbase[-4 * (2 * r - 1)];
#pragma unroll
      for (int k = 0; k < 16; k++) {
        const int dl = 8 * k + r;
        const uint32_t f0 = fbase[-4 * (2 * dl)];
        const uint32_t f1 = fbase[-4 * (2 * dl + 1)];
        if (k > 0) fm1 = fbase[-4 * (2 * dl - 1)];
#pragma unroll
        for (int j = k; j < 16; j++) mma_bf16(D[j], f0, f1, fm1, f0, B[j - k][0], B[j - k][1]);
      }
    }
  }
  __syncthreads();
  {
    bf16* ys = ks + warp * KCH;
#pragma unroll
    for (int j = 0; j < 16; j++) {
#pragma unroll
      for (int q = 0; q < 4; q++) {
        const int a = 8 * j + 2 * t + (q & 1), b = g + (q >> 1) * 8;
        ys[16 * a + b] = __float2bfloat16_rn(D[j][q]);
      }
    }
  }
  __syncthreads();
  {
    float dsk[CH];
#pragma unroll
    for (int c = 0; c < CH; c++) dsk[c] = __bfloat162float(Dskip[d0 + c]);
    for (int l = tid; l < SEQ; l += 256) {
      uint4 v = *reinterpret_cast<const uint4*>(x + (size_t)l * DM + d0);
      const bf16* p = reinterpret_cast<const bf16*>(&v);
      uint32_t o[4];
#pragma unroll
      for (int c = 0; c < CH; c += 2) {
        const float y0 = __bfloat162float(ks[c * KCH + l]), y1 = __bfloat162float(ks[(c + 1) * KCH + l]);
        const float b0 = y0 + bfr(__bfloat162float(p[c]) * dsk[c]);
        const float b1 = y1 + bfr(__bfloat162float(p[c + 1]) * dsk[c + 1]);
        o[c >> 1] = pack2(b0, b1);
      }
      *reinterpret_cast<uint4*>(g_b + (size_t)l * DM + d0) = make_uint4(o[0], o[1], o[2], o[3]);
    }
  }
}

typedef CUresult (*EncodeFn)(CUtensorMap*, CUtensorMapDataType, cuuint32_t, void*, const cuuint64_t*, const cuuint64_t*,
                             const cuuint32_t*, const cuuint32_t*, CUtensorMapInterleave, CUtensorMapSwizzle,
                             CUtensorMapL2promotion, CUtensorMapFloatOOBfill);

static void make_map(EncodeFn enc, CUtensorMap* m, void* ptr, uint64_t inner, uint64_t outer, uint32_t bi, uint32_t bo) {
  cuuint64_t dims[2] = {inner, outer};
  cuuint64_t strides[1] = {inner * 2};
  cuuint32_t box[2] = {bi, bo};
  cuuint32_t es[2] = {1, 1};
  enc(m, CU_TENSOR_MAP_DATA_TYPE_BFLOAT16, 2, ptr, dims, strides, box, es, CU_TENSOR_MAP_INTERLEAVE_NONE,
      CU_TENSOR_MAP_SWIZZLE_128B, CU_TENSOR_MAP_L2_PROMOTION_L2_256B, CU_TENSOR_MAP_FLOAT_OOB_FILL_NONE);
}

extern "C" void kernel_launch(void* const* d_in, const int* in_sizes, int n_in, void* d_out, int out_size) {
  const bf16* x = (const bf16*)d_in[0];
  const bf16* wqkv = (const bf16*)d_in[1];
  const bf16* wo = (const bf16*)d_in[2];
  const bf16* logAr = (const bf16*)d_in[4];
  const bf16* Aim = (const bf16*)d_in[5];
  const bf16* Cre = (const bf16*)d_in[6];
  const bf16* Cim = (const bf16*)d_in[7];
  const bf16* logdt = (const bf16*)d_in[8];
  const bf16* Dskip = (const bf16*)d_in[9];
  const bf16* gatew = (const bf16*)d_in[10];

  static EncodeFn enc = nullptr;
  static void* p_o = nullptr;
  if (!enc) {
    void* fn = nullptr;
    cudaDriverEntryPointQueryResult qr;
    cudaGetDriverEntryPoint("cuTensorMapEncodeTiled", &fn, cudaEnableDefault, &qr);
    enc = (EncodeFn)fn;
    cudaGetSymbolAddress(&p_o, g_o);
    cudaFuncSetAttribute(k1_qkv_attn, cudaFuncAttributeMaxDynamicSharedMemorySize, k1::SMEM);
    cudaFuncSetAttribute(k2_ssm, cudaFuncAttributeMaxDynamicSharedMemorySize, k2::SMEM);
    cudaFuncSetAttribute(k3_out, cudaFuncAttributeMaxDynamicSharedMemorySize, k3::SMEM);
  }
  CUtensorMap tmx, tmw, tmo, tmwo;
  make_map(enc, &tmx, (void*)x, 1024, 2048, 64, 128);
  make_map(enc, &tmw, (void*)wqkv, 3072, 1024, 64, 64);
  make_map(enc, &tmo, p_o, 1024, 2048, 64, 64);
  make_map(enc, &tmwo, (void*)wo, 1024, 1024, 64, 64);

  k2_ssm<<<128, 256, k2::SMEM>>>(x, logAr, Aim, Cre, Cim, logdt, Dskip, gatew);
  k1_qkv_attn<<<128, 384, k1::SMEM>>>(tmx, tmw);
  k3_out<<<128, 384, k3::SMEM>>>(tmo, tmwo, (bf16*)d_out);
}
```

```cpp
#include <cuda_runtime.h>
#include <cuda_bf16.h>
#include <cuda.h>
#include <stdint.h>

typedef __nv_bfloat16 bf16;

constexpr int SEQ = 2048, DM = 1024, NMODE = 128;

__device__ __align__(1024) bf16 g_o[SEQ * DM];
__device__ __align__(1024) bf16 g_b[SEQ * DM];
__device__ float g_gate[SEQ];
__device__ __align__(16) float g_part[16 * 8 * 2 * 1056];
__device__ unsigned int g_cnt[16];

__device__ __forceinline__ uint32_t smem_u32(const void* p) { return (uint32_t)__cvta_generic_to_shared(p); }
__device__ __forceinline__ void mbar_init(uint32_t bar, uint32_t cnt) {
  asm volatile("mbarrier.init.shared::cta.b64 [%0], %1;" ::"r"(bar), "r"(cnt));
}
__device__ __forceinline__ void mbar_expect_tx(uint32_t bar, uint32_t bytes) {
  asm volatile("mbarrier.arrive.expect_tx.shared::cta.b64 _, [%0], %1;" ::"r"(bar), "r"(bytes) : "memory");
}
__device__ __forceinline__ void mbar_arrive_cluster(uint32_t bar, uint32_t cta) {
  asm volatile(
      "{\n.reg .b32 ra;\nmapa.shared::cluster.u32 ra, %0, %1;\n"
      "mbarrier.arrive.shared::cluster.b64 _, [ra];\n}\n" ::"r"(bar), "r"(cta) : "memory");
}
__device__ __forceinline__ bool mbar_try_wait(uint32_t bar, uint32_t parity) {
  uint32_t ok;
  asm volatile(
      "{\n.reg .pred p;\nmbarrier.try_wait.parity.shared::cta.b64 p, [%1], %2;\nselp.u32 %0, 1, 0, p;\n}\n"
      : "=r"(ok) : "r"(bar), "r"(parity) : "memory");
  return ok;
}
__device__ __forceinline__ void mbar_wait(uint32_t bar, uint32_t parity) {
  while (!mbar_try_wait(bar, parity)) {}
}
__device__ __forceinline__ void tma_load_2d(uint32_t dst, const CUtensorMap* map, uint32_t bar, int c0, int c1) {
  asm volatile(
      "cp.async.bulk.tensor.2d.shared::cluster.global.mbarrier::complete_tx::bytes [%0], [%1, {%3, %4}], [%2];" ::"r"(dst),
      "l"(map), "r"(bar), "r"(c0), "r"(c1) : "memory");
}
__device__ __forceinline__ void tma_load_2d_mc(uint32_t dst, const CUtensorMap* map, uint32_t bar, int c0, int c1,
                                               uint16_t mask) {
  asm volatile(
      "cp.async.bulk.tensor.2d.shared::cluster.global.mbarrier::complete_tx::bytes.multicast::cluster [%0], [%1, {%3, %4}], [%2], %5;" ::"r"(dst),
      "l"(map), "r"(bar), "r"(c0), "r"(c1), "h"(mask) : "memory");
}
__device__ __forceinline__ void cluster_sync_all() {
  asm volatile("barrier.cluster.arrive.release.aligned;\nbarrier.cluster.wait.acquire.aligned;\n" ::: "memory");
}
__device__ __forceinline__ uint32_t cluster_ctarank() {
  uint32_t r; asm volatile("mov.u32 %0, %%cluster_ctarank;" : "=r"(r)); return r;
}
__device__ __forceinline__ void named_bar_sync(int id, int n) { asm volatile("bar.sync %0, %1;" ::"r"(id), "r"(n) : "memory"); }
__device__ __forceinline__ void fence_async_smem() { asm volatile("fence.proxy.async.shared::cta;" ::: "memory"); }
__device__ __forceinline__ void wg_fence() { asm volatile("wgmma.fence.sync.aligned;" ::: "memory"); }
__device__ __forceinline__ void wg_commit() { asm volatile("wgmma.commit_group.sync.aligned;" ::: "memory"); }
template <int N> __device__ __forceinline__ void wg_wait() { asm volatile("wgmma.wait_group.sync.aligned %0;" ::"n"(N) : "memory"); }
__device__ __forceinline__ uint64_t make_desc(uint32_t addr, uint32_t lbo, uint32_t sbo) {
  return (uint64_t)((addr & 0x3FFFF) >> 4) | ((uint64_t)(lbo >> 4) << 16) | ((uint64_t)(sbo >> 4) << 32) | (1ull << 62);
}
__device__ __forceinline__ float bfr(float x) { return __bfloat162float(__float2bfloat16_rn(x)); }
__device__ __forceinline__ uint32_t pack2(float lo, float hi) {
  __nv_bfloat162 v = __floats2bfloat162_rn(lo, hi);
  return *reinterpret_cast<uint32_t*>(&v);
}
__device__ __forceinline__ float ex2f(float x) { float r; asm("ex2.approx.ftz.f32 %0, %1;" : "=f"(r) : "f"(x)); return r; }
__device__ __forceinline__ float lo_f(uint32_t v) { return __uint_as_float(v << 16); }
__device__ __forceinline__ float hi_f(uint32_t v) { return __uint_as_float(v & 0xffff0000u); }
__device__ __forceinline__ uint32_t phi2(float a0, float a1) {
  const uint32_t t2 = pack2(a0, a1);
  const float t0 = lo_f(t2), t1 = hi_f(t2);
  const float e0 = ex2f(t0 * 1.4426950408889634f), e1 = ex2f(t1 * 1.4426950408889634f);
  const float f0 = t0 > 0.f ? t0 + 1.0f : e0;
  const float f1 = t1 > 0.f ? t1 + 1.0f : e1;
  const uint32_t f2 = pack2(f0, f1);
  return pack2(lo_f(f2) + 1e-6f, hi_f(f2) + 1e-6f);
}
template <int R> __device__ __forceinline__ void fence_regs(float (&d)[R]) {
#pragma unroll
  for (int i = 0; i < R; i++) asm volatile("" : "+f"(d[i])::"memory");
}

__device__ __forceinline__ void wgmma_ss_n192_tb(float (&d)[96], uint64_t da, uint64_t db, int sc) {
  asm volatile("{\n.reg .pred p;\nsetp.ne.b32 p, %98, 0;\n"
    "wgmma.mma_async.sync.aligned.m64n192k16.f32.bf16.bf16 {%0, %1, %2, %3, %4, %5, %6, %7, %8, %9, %10, %11, %12, %13, %14, %15, %16, %17, %18, %19, %20, %21, %22, %23, %24, %25, %26, %27, %28, %29, %30, %31, %32, %33, %34, %35, %36, %37, %38, %39, %40, %41, %42, %43, %44, %45, %46, %47, %48, %49, %50, %51, %52, %53, %54, %55, %56, %57, %58, %59, %60, %61, %62, %63, %64, %65, %66, %67, %68, %69, %70, %71, %72, %73, %74, %75, %76, %77, %78, %79, %80, %81, %82, %83, %84, %85, %86, %87, %88, %89, %90, %91, %92, %93, %94, %95}, %96, %97, p, 1, 1, 0, 1;\n}\n"
    : "+f"(d[0]), "+f"(d[1]), "+f"(d[2]), "+f"(d[3]), "+f"(d[4]), "+f"(d[5]), "+f"(d[6]), "+f"(d[7]), "+f"(d[8]), "+f"(d[9]), "+f"(d[10]), "+f"(d[11]), "+f"(d[12]), "+f"(d[13]), "+f"(d[14]), "+f"(d[15]), "+f"(d[16]), "+f"(d[17]), "+f"(d[18]), "+f"(d[19]), "+f"(d[20]), "+f"(d[21]), "+f"(d[22]), "+f"(d[23]), "+f"(d[24]), "+f"(d[25]), "+f"(d[26]), "+f"(d[27]), "+f"(d[28]), "+f"(d[29]), "+f"(d[30]), "+f"(d[31]), "+f"(d[32]), "+f"(d[33]), "+f"(d[34]), "+f"(d[35]), "+f"(d[36]), "+f"(d[37]), "+f"(d[38]), "+f"(d[39]), "+f"(d[40]), "+f"(d[41]), "+f"(d[42]), "+f"(d[43]), "+f"(d[44]), "+f"(d[45]), "+f"(d[46]), "+f"(d[47]), "+f"(d[48]), "+f"(d[49]), "+f"(d[50]), "+f"(d[51]), "+f"(d[52]), "+f"(d[53]), "+f"(d[54]), "+f"(d[55]), "+f"(d[56]), "+f"(d[57]), "+f"(d[58]), "+f"(d[59]), "+f"(d[60]), "+f"(d[61]), "+f"(d[62]), "+f"(d[63]), "+f"(d[64]), "+f"(d[65]), "+f"(d[66]), "+f"(d[67]), "+f"(d[68]), "+f"(d[69]), "+f"(d[70]), "+f"(d[71]), "+f"(d[72]), "+f"(d[73]), "+f"(d[74]), "+f"(d[75]), "+f"(d[76]), "+f"(d[77]), "+f"(d[78]), "+f"(d[79]), "+f"(d[80]), "+f"(d[81]), "+f"(d[82]), "+f"(d[83]), "+f"(d[84]), "+f"(d[85]), "+f"(d[86]), "+f"(d[87]), "+f"(d[88]), "+f"(d[89]), "+f"(d[90]), "+f"(d[91]), "+f"(d[92]), "+f"(d[93]), "+f"(d[94]), "+f"(d[95])
    : "l"(da), "l"(db), "r"(sc));
}

__device__ __forceinline__ void wgmma_ss_n128_tb(float (&d)[64], uint64_t da, uint64_t db, int sc) {
  asm volatile("{\n.reg .pred p;\nsetp.ne.b32 p, %66, 0;\n"
    "wgmma.mma_async.sync.aligned.m64n128k16.f32.bf16.bf16 {%0, %1, %2, %3, %4, %5, %6, %7, %8, %9, %10, %11, %12, %13, %14, %15, %16, %17, %18, %19, %20, %21, %22, %23, %24, %25, %26, %27, %28, %29, %30, %31, %32, %33, %34, %35, %36, %37, %38, %39, %40, %41, %42, %43, %44, %45, %46, %47, %48, %49, %50, %51, %52, %53, %54, %55, %56, %57, %58, %59, %60, %61, %62, %63}, %64, %65, p, 1, 1, 0, 1;\n}\n"
    : "+f"(d[0]), "+f"(d[1]), "+f"(d[2]), "+f"(d[3]), "+f"(d[4]), "+f"(d[5]), "+f"(d[6]), "+f"(d[7]), "+f"(d[8]), "+f"(d[9]), "+f"(d[10]), "+f"(d[11]), "+f"(d[12]), "+f"(d[13]), "+f"(d[14]), "+f"(d[15]), "+f"(d[16]), "+f"(d[17]), "+f"(d[18]), "+f"(d[19]), "+f"(d[20]), "+f"(d[21]), "+f"(d[22]), "+f"(d[23]), "+f"(d[24]), "+f"(d[25]), "+f"(d[26]), "+f"(d[27]), "+f"(d[28]), "+f"(d[29]), "+f"(d[30]), "+f"(d[31]), "+f"(d[32]), "+f"(d[33]), "+f"(d[34]), "+f"(d[35]), "+f"(d[36]), "+f"(d[37]), "+f"(d[38]), "+f"(d[39]), "+f"(d[40]), "+f"(d[41]), "+f"(d[42]), "+f"(d[43]), "+f"(d[44]), "+f"(d[45]), "+f"(d[46]), "+f"(d[47]), "+f"(d[48]), "+f"(d[49]), "+f"(d[50]), "+f"(d[51]), "+f"(d[52]), "+f"(d[53]), "+f"(d[54]), "+f"(d[55]), "+f"(d[56]), "+f"(d[57]), "+f"(d[58]), "+f"(d[59]), "+f"(d[60]), "+f"(d[61]), "+f"(d[62]), "+f"(d[63])
    : "l"(da), "l"(db), "r"(sc));
}

__device__ __forceinline__ void wgmma_ss_n64_tatb(float (&d)[32], uint64_t da, uint64_t db, int sc) {
  asm volatile("{\n.reg .pred p;\nsetp.ne.b32 p, %34, 0;\n"
    "wgmma.mma_async.sync.aligned.m64n64k16.f32.bf16.bf16 {%0, %1, %2, %3, %4, %5, %6, %7, %8, %9, %10, %11, %12, %13, %14, %15, %16, %17, %18, %19, %20, %21, %22, %23, %24, %25, %26, %27, %28, %29, %30, %31}, %32, %33, p, 1, 1, 1, 1;\n}\n"
    : "+f"(d[0]), "+f"(d[1]), "+f"(d[2]), "+f"(d[3]), "+f"(d[4]), "+f"(d[5]), "+f"(d[6]), "+f"(d[7]), "+f"(d[8]), "+f"(d[9]), "+f"(d[10]), "+f"(d[11]), "+f"(d[12]), "+f"(d[13]), "+f"(d[14]), "+f"(d[15]), "+f"(d[16]), "+f"(d[17]), "+f"(d[18]), "+f"(d[19]), "+f"(d[20]), "+f"(d[21]), "+f"(d[22]), "+f"(d[23]), "+f"(d[24]), "+f"(d[25]), "+f"(d[26]), "+f"(d[27]), "+f"(d[28]), "+f"(d[29]), "+f"(d[30]), "+f"(d[31])
    : "l"(da), "l"(db), "r"(sc));
}

__device__ __forceinline__ void wgmma_ss_n8_tatb(float (&d)[4], uint64_t da, uint64_t db, int sc) {
  asm volatile("{\n.reg .pred p;\nsetp.ne.b32 p, %6, 0;\n"
    "wgmma.mma_async.sync.aligned.m64n8k16.f32.bf16.bf16 {%0, %1, %2, %3}, %4, %5, p, 1, 1, 1, 1;\n}\n"
    : "+f"(d[0]), "+f"(d[1]), "+f"(d[2]), "+f"(d[3])
    : "l"(da), "l"(db), "r"(sc));
}

__device__ __forceinline__ void wgmma_rs_n40_tb(float (&d)[20], uint32_t a0, uint32_t a1, uint32_t a2, uint32_t a3, uint64_t db, int sc) {
  asm volatile("{\n.reg .pred p;\nsetp.ne.b32 p, %25, 0;\n"
    "wgmma.mma_async.sync.aligned.m64n40k16.f32.bf16.bf16 {%0, %1, %2, %3, %4, %5, %6, %7, %8, %9, %10, %11, %12, %13, %14, %15, %16, %17, %18, %19}, {%20, %21, %22, %23}, %24, p, 1, 1, 1;\n}\n"
    : "+f"(d[0]), "+f"(d[1]), "+f"(d[2]), "+f"(d[3]), "+f"(d[4]), "+f"(d[5]), "+f"(d[6]), "+f"(d[7]), "+f"(d[8]), "+f"(d[9]), "+f"(d[10]), "+f"(d[11]), "+f"(d[12]), "+f"(d[13]), "+f"(d[14]), "+f"(d[15]), "+f"(d[16]), "+f"(d[17]), "+f"(d[18]), "+f"(d[19])
    : "r"(a0), "r"(a1), "r"(a2), "r"(a3), "l"(db), "r"(sc));
}


namespace k1 {
constexpr int BM = 256, BN = 192, BK = 64, ST = 4;
constexpr int A_BYTES = BM * BK * 2, B_BYTES = BK * BN * 2, STAGE = A_BYTES + B_BYTES;
constexpr int SMEM = ST * STAGE + 1024 + 256;
constexpr int OFF_PK = 0, OFF_V = 32768, OFF_ONES = 65536, OFF_KV = 69632, OFF_O = 81920, OFF_RED = 114688;
}

__global__ void __cluster_dims__(2, 1, 1) __launch_bounds__(384, 1)
k1_qkv_attn(const __grid_constant__ CUtensorMap tmx, const __grid_constant__ CUtensorMap tmw) {
  using namespace k1;
  extern __shared__ uint8_t smem_raw[];
  const uint32_t sbase = (smem_u32(smem_raw) + 1023) & ~1023u;
  uint8_t* sgen = smem_raw + (sbase - smem_u32(smem_raw));
  const uint32_t bars = sbase + ST * STAGE;
  const int tid = threadIdx.x, warp = tid >> 5, lane = tid & 31;
  const uint32_t rank = cluster_ctarank();
  const int cl = blockIdx.x >> 1;
  const int mt = cl >> 3;
  const int hp = ((cl & 7) << 1) + rank;
  const int m0 = mt * BM;

  if (tid == 0) {
    for (int s = 0; s < ST; s++) {
      mbar_init(bars + 8 * s, 1);
      mbar_init(bars + 8 * (ST + s), 16);
    }
    asm volatile("fence.mbarrier_init.release.cluster;" ::: "memory");
  }
  cluster_sync_all();

  if (warp >= 8) {
    asm volatile("setmaxnreg.dec.sync.aligned.u32 40;");
    if (warp == 8 && lane == 0) {
      for (int kb = 0; kb < DM / BK; kb++) {
        const int s = kb % ST;
        mbar_wait(bars + 8 * (ST + s), ((kb / ST) & 1) ^ 1);
        const uint32_t full = bars + 8 * s;
        mbar_expect_tx(full, STAGE);
        const uint32_t sa = sbase + s * STAGE, sb = sa + A_BYTES;
        tma_load_2d_mc(sa + rank * 16384, &tmx, full, kb * BK, m0 + rank * 128, (uint16_t)3);
#pragma unroll
        for (int j = 0; j < 3; j++) tma_load_2d(sb + j * 8192, &tmw, full, j * 1024 + hp * 64, kb * BK);
      }
    }
    cluster_sync_all();
  } else {
    asm volatile("setmaxnreg.inc.sync.aligned.u32 232;");
    const int wg = warp >> 2, w4 = warp & 3, g = lane >> 2, t = lane & 3;
    float acc[2][96];
#pragma unroll
    for (int i = 0; i < 96; i++) { acc[0][i] = 0.f; acc[1][i] = 0.f; }
    for (int kb = 0; kb < DM / BK; kb++) {
      const int s = kb % ST;
      mbar_wait(bars + 8 * s, (kb / ST) & 1);
      const uint32_t sa = sbase + s * STAGE + wg * 16384, sb = sbase + s * STAGE + A_BYTES;
      wg_fence();
#pragma unroll
      for (int ks = 0; ks < 4; ks++) {
        const uint64_t db = make_desc(sb + ks * 2048, 8192, 1024);
#pragma unroll
        for (int mb = 0; mb < 2; mb++) {
          const uint64_t da = make_desc(sa + mb * 8192 + ks * 32, 16, 1024);
          wgmma_ss_n192_tb(acc[mb], da, db, 1);
        }
      }
      wg_commit();
      if (kb > 0) {
        wg_wait<1>();
        const int sp = (kb - 1) % ST;
        if (lane == 0) { mbar_arrive_cluster(bars + 8 * (ST + sp), 0); mbar_arrive_cluster(bars + 8 * (ST + sp), 1); }
      }
    }
    wg_wait<0>();
    fence_regs(acc[0]); fence_regs(acc[1]);
    named_bar_sync(1, 256);

#pragma unroll
    for (int mb = 0; mb < 2; mb++) {
#pragma unroll
      for (int h = 0; h < 2; h++) {
        const int r = wg * 128 + mb * 64 + w4 * 16 + g + h * 8;
#pragma unroll
        for (int j = 0; j < 8; j++) {
          const uint32_t off = r * 128 + ((j ^ (r & 7)) << 4) + t * 4;
          const float k0 = acc[mb][4 * (8 + j) + 2 * h], k1v = acc[mb][4 * (8 + j) + 2 * h + 1];
          const float v0 = acc[mb][4 * (16 + j) + 2 * h], v1 = acc[mb][4 * (16 + j) + 2 * h + 1];
          *reinterpret_cast<uint32_t*>(sgen + OFF_PK + off) = phi2(k0, k1v);
          *reinterpret_cast<uint32_t*>(sgen + OFF_V + off) = pack2(v0, v1);
        }
      }
    }
    if (tid < 256) *reinterpret_cast<uint32_t*>(sgen + OFF_ONES + tid * 4) = 0x3F803F80u;
    fence_async_smem();
    named_bar_sync(1, 256);

    float* part = g_part + (size_t)(hp * 8 + mt) * 2112;
    {
      float kv[32], zz[4];
#pragma unroll
      for (int i = 0; i < 32; i++) kv[i] = 0.f;
#pragma unroll
      for (int i = 0; i < 4; i++) zz[i] = 0.f;
      wg_fence();
#pragma unroll
      for (int ks = 0; ks < 8; ks++) {
        const uint64_t da = make_desc(sbase + OFF_PK + wg * 16384 + ks * 2048, 16, 1024);
        const uint64_t db = make_desc(sbase + OFF_V + wg * 16384 + ks * 2048, 16, 1024);
        const uint64_t d1 = make_desc(sbase + OFF_ONES, 16, 0);
        wgmma_ss_n64_tatb(kv, da, db, 1);
        wgmma_ss_n8_tatb(zz, da, d1, 1);
      }
      wg_commit();
      wg_wait<0>();
      fence_regs(kv); fence_regs(zz);
      const int hh = w4 >> 1;
      float* red = reinterpret_cast<float*>(sgen + OFF_RED);
      float vals[2][4][2];
#pragma unroll
      for (int h = 0; h < 2; h++)
#pragma unroll
        for (int j = 0; j < 4; j++) {
          vals[h][j][0] = hh ? kv[4 * (4 + j) + 2 * h] : kv[4 * j + 2 * h];
          vals[h][j][1] = hh ? kv[4 * (4 + j) + 2 * h + 1] : kv[4 * j + 2 * h + 1];
        }
      if (wg == 1) {
#pragma unroll
        for (int h = 0; h < 2; h++) {
          const int d = (w4 & 1) * 16 + g + h * 8;
#pragma unroll
          for (int j = 0; j < 4; j++)
            *reinterpret_cast<float2*>(red + hh * 1056 + d * 32 + 8 * j + 2 * t) = make_float2(vals[h][j][0], vals[h][j][1]);
          if (t == 0) red[hh * 1056 + 1024 + d] = zz[2 * h];
        }
      }
      named_bar_sync(1, 256);
      if (wg == 0) {
#pragma unroll
        for (int h = 0; h < 2; h++) {
          const int d = (w4 & 1) * 16 + g + h * 8;
#pragma unroll
          for (int j = 0; j < 4; j++) {
            const float2 o = *reinterpret_cast<const float2*>(red + hh * 1056 + d * 32 + 8 * j + 2 * t);
            *reinterpret_cast<float2*>(part + hh * 1056 + d * 32 + 8 * j + 2 * t) = make_float2(vals[h][j][0] + o.x, vals[h][j][1] + o.y);
          }
          if (t == 0) part[hh * 1056 + 1024 + d] = zz[2 * h] + red[hh * 1056 + 1024 + d];
        }
        __threadfence();
        named_bar_sync(2, 128);
        if (tid == 0) atomicAdd(&g_cnt[hp], 1u);
      }
    }
    uint32_t pq[2][4][4];
#pragma unroll
    for (int mb = 0; mb < 2; mb++)
#pragma unroll
      for (int kk = 0; kk < 4; kk++) {
        pq[mb][kk][0] = phi2(acc[mb][8 * kk + 0], acc[mb][8 * kk + 1]);
        pq[mb][kk][1] = phi2(acc[mb][8 * kk + 2], acc[mb][8 * kk + 3]);
        pq[mb][kk][2] = phi2(acc[mb][8 * kk + 4], acc[mb][8 * kk + 5]);
        pq[mb][kk][3] = phi2(acc[mb][8 * kk + 6], acc[mb][8 * kk + 7]);
      }
    if (tid == 0) {
      unsigned int v;
      do { asm volatile("ld.acquire.gpu.global.u32 %0, [%1];" : "=r"(v) : "l"(&g_cnt[hp]) : "memory"); } while (v < 8u);
    }
    named_bar_sync(1, 256);
    {
      const float* pb = g_part + (size_t)(hp * 8) * 2112;
      for (int i = tid; i < 528; i += 256) {
        float4 s4 = make_float4(0.f, 0.f, 0.f, 0.f);
#pragma unroll
        for (int p = 0; p < 8; p++) {
          float4 v4 = __ldcg(reinterpret_cast<const float4*>(pb + p * 2112) + i);
          s4.x += v4.x; s4.y += v4.y; s4.z += v4.z; s4.w += v4.w;
        }
        const int hh = i / 264, rem = i - hh * 264;
        uint8_t* tile = sgen + OFF_KV + hh * 4096;
        if (rem < 256) {
          const int d = rem >> 3, e = (rem & 7) * 4;
          const uint32_t off = d * 128 + (((e >> 3) ^ (d & 7)) << 4) + (e & 7) * 2;
          *reinterpret_cast<uint2*>(tile + off) = make_uint2(pack2(s4.x, s4.y), pack2(s4.z, s4.w));
        } else {
          const int d0 = (rem - 256) * 4;
          float zv[4] = {s4.x, s4.y, s4.z, s4.w};
#pragma unroll
          for (int q = 0; q < 4; q++) {
            const int d = d0 + q;
            const uint32_t off = d * 128 + ((4 ^ (d & 7)) << 4);
            *reinterpret_cast<uint4*>(tile + off) = make_uint4(pack2(zv[q], 0.f), 0u, 0u, 0u);
          }
        }
      }
    }
    fence_async_smem();
    named_bar_sync(1, 256);
#pragma unroll
    for (int mb = 0; mb < 2; mb++) {
#pragma unroll
      for (int hh = 0; hh < 2; hh++) {
        float num[20];
#pragma unroll
        for (int i = 0; i < 20; i++) num[i] = 0.f;
        wg_fence();
#pragma unroll
        for (int kk = 0; kk < 2; kk++) {
          const uint64_t db = make_desc(sbase + OFF_KV + hh * 4096 + kk * 2048, 16, 1024);
          wgmma_rs_n40_tb(num, pq[mb][hh * 2 + kk][0], pq[mb][hh * 2 + kk][1], pq[mb][hh * 2 + kk][2], pq[mb][hh * 2 + kk][3], db, 1);
        }
        wg_commit();
        wg_wait<0>();
        fence_regs(num);
#pragma unroll
        for (int h = 0; h < 2; h++) {
          float den = __shfl_sync(0xffffffffu, num[16 + 2 * h], lane & ~3);
          den = bfr(bfr(den) + 1e-6f);
          const float rden = 1.0f / den;
          const int r = wg * 128 + mb * 64 + w4 * 16 + g + h * 8;
#pragma unroll
          for (int j = 0; j < 4; j++) {
            const uint32_t n2 = pack2(num[4 * j + 2 * h], num[4 * j + 2 * h + 1]);
            const float o0 = lo_f(n2) * rden, o1 = hi_f(n2) * rden;
            const uint32_t off = r * 128 + (((hh * 4 + j) ^ (r & 7)) << 4) + t * 4;
            *reinterpret_cast<uint32_t*>(sgen + OFF_O + off) = pack2(o0, o1);
          }
        }
      }
    }
    named_bar_sync(1, 256);
    for (int i = tid; i < 256 * 8; i += 256) {
      const int r = i >> 3, c = i & 7;
      uint4 v = *reinterpret_cast<const uint4*>(sgen + OFF_O + r * 128 + ((c ^ (r & 7)) << 4));
      *reinterpret_cast<uint4*>(g_o + (size_t)(m0 + r) * DM + hp * 64 + c * 8) = v;
    }
    cluster_sync_all();
  }
}

namespace k3 {
constexpr int BM = 128, BN = 128, BK = 64, ST = 6;
constexpr int A_BYTES = BM * BK * 2, B_BYTES = BK * BN * 2, STAGE = A_BYTES + B_BYTES;
constexpr int SMEM = ST * STAGE + 1024 + 256;
}

__global__ void __cluster_dims__(2, 1, 1) __launch_bounds__(384, 1)
k3_out(const __grid_constant__ CUtensorMap tmo, const __grid_constant__ CUtensorMap tmw, bf16* __restrict__ out) {
  using namespace k3;
  extern __shared__ uint8_t smem_raw[];
  const uint32_t sbase = (smem_u32(smem_raw) + 1023) & ~1023u;
  const uint32_t bars = sbase + ST * STAGE;
  const int tid = threadIdx.x, warp = tid >> 5, lane = tid & 31;
  const uint32_t rank = cluster_ctarank();
  const int cl = blockIdx.x >> 1;
  const int mt = cl >> 2;
  const int nt = ((cl & 3) << 1) + rank;
  const int m0 = mt * BM, n0 = nt * BN;
  if (blockIdx.x == 0 && tid < 16) g_cnt[tid] = 0;

  if (tid == 0) {
    for (int s = 0; s < ST; s++) {
      mbar_init(bars + 8 * s, 1);
      mbar_init(bars + 8 * (ST + s), 16);
    }
    asm volatile("fence.mbarrier_init.release.cluster;" ::: "memory");
  }
  cluster_sync_all();

  if (warp >= 8) {
    asm volatile("setmaxnreg.dec.sync.aligned.u32 40;");
    if (warp == 8 && lane == 0) {
      for (int kb = 0; kb < DM / BK; kb++) {
        const int s = kb % ST;
        mbar_wait(bars + 8 * (ST + s), ((kb / ST) & 1) ^ 1);
        const uint32_t full = bars + 8 * s;
        mbar_expect_tx(full, STAGE);
        const uint32_t sa = sbase + s * STAGE, sb = sa + A_BYTES;
        tma_load_2d_mc(sa + rank * 8192, &tmo, full, kb * BK, m0 + rank * 64, (uint16_t)3);
#pragma unroll
        for (int j = 0; j < 2; j++) tma_load_2d(sb + j * 8192, &tmw, full, n0 + j * 64, kb * BK);
      }
    }
    cluster_sync_all();
  } else {
    asm volatile("setmaxnreg.inc.sync.aligned.u32 232;");
    const int wg = warp >> 2, w4 = warp & 3, g = lane >> 2, t = lane & 3;
    float acc[64];
#pragma unroll
    for (int i = 0; i < 64; i++) acc[i] = 0.f;
    for (int kb = 0; kb < DM / BK; kb++) {
      const int s = kb % ST;
      mbar_wait(bars + 8 * s, (kb / ST) & 1);
      const uint32_t sa = sbase + s * STAGE + wg * 8192, sb = sbase + s * STAGE + A_BYTES;
      wg_fence();
#pragma unroll
      for (int ks = 0; ks < 4; ks++) {
        const uint64_t db = make_desc(sb + ks * 2048, 8192, 1024);
        const uint64_t da = make_desc(sa + ks * 32, 16, 1024);
        wgmma_ss_n128_tb(acc, da, db, 1);
      }
      wg_commit();
      if (kb > 0) {
        wg_wait<1>();
        const int sp = (kb - 1) % ST;
        if (lane == 0) { mbar_arrive_cluster(bars + 8 * (ST + sp), 0); mbar_arrive_cluster(bars + 8 * (ST + sp), 1); }
      }
    }
    wg_wait<0>();
    fence_regs(acc);
#pragma unroll
    for (int h = 0; h < 2; h++) {
      const int r = m0 + wg * 64 + w4 * 16 + g + h * 8;
      const float gt = g_gate[r];
      const float omg = bfr(1.0f - gt);
#pragma unroll
      for (int j = 0; j < 16; j++) {
        const int c = n0 + 8 * j + 2 * t;
        const __nv_bfloat162 bb = *reinterpret_cast<const __nv_bfloat162*>(g_b + (size_t)r * DM + c);
        const float o0 = bfr(gt * bfr(acc[4 * j + 2 * h])) + bfr(omg * __bfloat162float(bb.x));
        const float o1 = bfr(gt * bfr(acc[4 * j + 2 * h + 1])) + bfr(omg * __bfloat162float(bb.y));
        *reinterpret_cast<uint32_t*>(out + (size_t)r * DM + c) = pack2(o0, o1);
      }
    }
    cluster_sync_all();
  }
}

namespace k2 {
constexpr int CH = 8;
constexpr int UPAD = 128;
constexpr int USZ = UPAD + SEQ;
constexpr int KOFF = 2048 + 16;
constexpr int KSZ = 2112;
constexpr int KCH = 2 * KSZ + 16;
constexpr int OFF_U = 0;
constexpr int OFF_K = OFF_U + CH * USZ * 2;
constexpr int OFF_KQ = OFF_K + CH * KCH * 2;
constexpr int SMEM = OFF_KQ + CH * 648 * 4;
}

__device__ __forceinline__ void mma_bf16(float (&d)[4], uint32_t a0, uint32_t a1, uint32_t a2, uint32_t a3, uint32_t b0, uint32_t b1) {
  asm volatile("mma.sync.aligned.m16n8k16.row.col.f32.bf16.bf16.f32 {%0,%1,%2,%3}, {%4,%5,%6,%7}, {%8,%9}, {%0,%1,%2,%3};"
               : "+f"(d[0]), "+f"(d[1]), "+f"(d[2]), "+f"(d[3]) : "r"(a0), "r"(a1), "r"(a2), "r"(a3), "r"(b0), "r"(b1));
}
__device__ __forceinline__ void mma_tf32(float (&d)[4], uint32_t a0, uint32_t a1, uint32_t a2, uint32_t a3, uint32_t b0, uint32_t b1) {
  asm volatile("mma.sync.aligned.m16n8k8.row.col.f32.tf32.tf32.f32 {%0,%1,%2,%3}, {%4,%5,%6,%7}, {%8,%9}, {%0,%1,%2,%3};"
               : "+f"(d[0]), "+f"(d[1]), "+f"(d[2]), "+f"(d[3]) : "r"(a0), "r"(a1), "r"(a2), "r"(a3), "r"(b0), "r"(b1));
}
__device__ __forceinline__ uint32_t tf32r(float x) { uint32_t r; asm("cvt.rna.tf32.f32 %0, %1;" : "=r"(r) : "f"(x)); return r; }
struct cf { float r, i; };
__device__ __forceinline__ cf cmul(cf a, cf b) { cf c; c.r = a.r * b.r - a.i * b.i; c.i = a.r * b.i + a.i * b.r; return c; }
__device__ __forceinline__ cf csq(cf a) { cf c; c.r = a.r * a.r - a.i * a.i; c.i = 2.f * a.r * a.i; return c; }
__device__ __forceinline__ cf cexpp(float ar, float ai, float p) {
  const float e = ex2f(ar * p * 1.4426950408889634f);
  const float th = ai * p;
  const float k = rintf(th * 0.15915494309189535f);
  float r = fmaf(k, -6.2831854820251465f, th);
  r = fmaf(k, 1.7484556000744e-7f, r);
  cf w; w.r = e * __cosf(r); w.i = e * __sinf(r); return w;
}

__global__ void __launch_bounds__(256, 1)
k2_ssm(const bf16* __restrict__ x, const bf16* __restrict__ logAr, const bf16* __restrict__ Aim, const bf16* __restrict__ Cre,
       const bf16* __restrict__ Cim, const bf16* __restrict__ logdt, const bf16* __restrict__ Dskip,
       const bf16* __restrict__ gatew) {
  using namespace k2;
  extern __shared__ __align__(16) uint8_t sm[];
  const int tid = threadIdx.x, warp = tid >> 5, lane = tid & 31, g = lane >> 2, t = lane & 3;
  const int d0 = blockIdx.x * CH;
  bf16* us = reinterpret_cast<bf16*>(sm + OFF_U);
  bf16* ks = reinterpret_cast<bf16*>(sm + OFF_K);
  float* kq = reinterpret_cast<float*>(sm + OFF_KQ);

  for (int rr = 0; rr < 2; rr++) {
    const int r = blockIdx.x * 16 + warp * 2 + rr;
    float s = 0.f;
    for (int c = lane * 8; c < DM; c += 256) {
      uint4 xv = *reinterpret_cast<const uint4*>(x + (size_t)r * DM + c);
      uint4 wv = *reinterpret_cast<const uint4*>(gatew + c);
      const bf16* xp = reinterpret_cast<const bf16*>(&xv);
      const bf16* wp = reinterpret_cast<const bf16*>(&wv);
#pragma unroll
      for (int q = 0; q < 8; q++) s += bfr(__bfloat162float(xp[q]) * __bfloat162float(wp[q]));
    }
#pragma unroll
    for (int o = 16; o; o >>= 1) s += __shfl_xor_sync(0xffffffffu, s, o);
    if (lane == 0) { float z = bfr(s); g_gate[r] = bfr(1.0f / (1.0f + expf(-z))); }
  }

  for (int i = tid; i < CH * UPAD / 2; i += 256) {
    const int c = i / (UPAD / 2), o = i % (UPAD / 2);
    reinterpret_cast<uint32_t*>(us + c * USZ)[o] = 0u;
  }
  for (int l = tid; l < SEQ; l += 256) {
    uint4 v = *reinterpret_cast<const uint4*>(x + (size_t)l * DM + d0);
    const bf16* p = reinterpret_cast<const bf16*>(&v);
    const int e = l & 15;
    const int pe = ((e & 7) >> 1) * 4 + (e >> 3) * 2 + (e & 1);
    const int pos = UPAD + (l & ~15) + pe;
#pragma unroll
    for (int c = 0; c < CH; c++) us[c * USZ + pos] = p[c];
  }

  {
    const int d = d0 + warp;
    const float dt = bfr(expf(__bfloat162float(logdt[d])));
    float acc[5][4];
#pragma unroll
    for (int a = 0; a < 5; a++)
#pragma unroll
      for (int b = 0; b < 4; b++) acc[a][b] = 0.f;
    float last = 0.f;
    for (int n0 = 0; n0 < NMODE; n0 += 4) {
      const int idx = d * NMODE + n0 + t;
      const float ar = -bfr(expf(__bfloat162float(logAr[idx]))) * dt;
      const float ai = __bfloat162float(Aim[idx]) * dt;
      cf C; C.r = __bfloat162float(Cre[idx]) * dt; C.i = __bfloat162float(Cim[idx]) * dt;
      const cf Y1 = cexpp(ar, ai, (float)g);
      const cf Y8 = cexpp(ar, ai, (float)(8 * g));
      const cf W64 = cexpp(ar, ai, 64.f);
      const cf Y2 = csq(Y1), Y4 = csq(Y2);
      const cf Y16 = csq(Y8), Y32 = csq(Y16), Y64 = csq(Y32);
      const cf W128 = csq(W64), W256 = csq(W128), W512 = csq(W256), W1024 = csq(W512);
      const cf X0a = cmul(C, Y8), X0b = cmul(X0a, W64);
      const cf X1a = cmul(X0a, W128), X1b = cmul(X0b, W128);
      const cf X2a = cmul(cmul(C, W256), Y16), X2b = cmul(X2a, W128);
      const cf X3a = cmul(cmul(C, W512), Y32), X3b = cmul(X3a, W256);
      const cf C4 = cmul(C, W1024);
      const cf X4a = cmul(C4, Y64), X4b = cmul(X4a, W512);
      last += C4.r * W1024.r - C4.i * W1024.i;
      const uint32_t y1r = tf32r(Y1.r), y1i = tf32r(Y1.i);
      mma_tf32(acc[0], tf32r(X0a.r), tf32r(X0b.r), tf32r(-X0a.i), tf32r(-X0b.i), y1r, y1i);
      mma_tf32(acc[1], tf32r(X1a.r), tf32r(X1b.r), tf32r(-X1a.i), tf32r(-X1b.i), y1r, y1i);
      mma_tf32(acc[2], tf32r(X2a.r), tf32r(X2b.r), tf32r(-X2a.i), tf32r(-X2b.i), tf32r(Y2.r), tf32r(Y2.i));
      mma_tf32(acc[3], tf32r(X3a.r), tf32r(X3b.r), tf32r(-X3a.i), tf32r(-X3b.i), tf32r(Y4.r), tf32r(Y4.i));
      mma_tf32(acc[4], tf32r(X4a.r), tf32r(X4b.r), tf32r(-X4a.i), tf32r(-X4b.i), tf32r(Y8.r), tf32r(Y8.i));
    }
    float* kqc = kq + warp * 648;
#pragma unroll
    for (int a = 0; a < 5; a++) {
      kqc[128 * a + 8 * g + 2 * t] = 2.f * acc[a][0];
      kqc[128 * a + 8 * g + 2 * t + 1] = 2.f * acc[a][1];
      kqc[128 * a + 8 * (g + 8) + 2 * t] = 2.f * acc[a][2];
      kqc[128 * a + 8 * (g + 8) + 2 * t + 1] = 2.f * acc[a][3];
    }
    last += __shfl_xor_sync(0xffffffffu, last, 1);
    last += __shfl_xor_sync(0xffffffffu, last, 2);
    if (lane == 0) kqc[640] = 2.f * last;
    __syncwarp();
    bf16* kr = ks + warp * KCH;
    bf16* kr2 = kr + KSZ + 16;
    for (int i = lane; i < KSZ; i += 32) {
      const int xk = KOFF - i;
      float v = 0.f;
      if (xk >= 0 && xk < SEQ) {
        const uint32_t pb = __float_as_uint(bfr((float)xk));
        int id;
        if (xk < 256) id = xk;
        else { const int e = (int)(pb >> 23) - 127; const int q = 128 + ((pb >> 16) & 127); id = 256 + (e - 8) * 128 + (q - 128); }
        v = kqc[id];
      }
      const bf16 bv = __float2bfloat16_rn(v);
      kr[i] = bv;
      if (i > 0) kr2[i - 1] = bv;
    }
    if (lane == 0) kr2[KSZ - 1] = __float2bfloat16_rn(0.f);
  }
  __syncthreads();

  float D[16][4];
#pragma unroll
  for (int j = 0; j < 16; j++)
#pragma unroll
    for (int q = 0; q < 4; q++) D[j][q] = 0.f;
  {
    const bf16* uc = us + warp * USZ + UPAD;
    const bf16* kr = ks + warp * KCH;
    const uint32_t* fbase = reinterpret_cast<const uint32_t*>((g & 1) ? (kr + KSZ + 16) : kr) + ((KOFF - g + 2 * t) >> 1);
    for (int r = 0; r < 8; r++) {
      uint32_t B[16][2];
#pragma unroll
      for (int j = 0; j < 16; j++) {
        const uint2 v = *reinterpret_cast<const uint2*>(uc + 16 * (8 * j - r + g) + 4 * t);
        B[j][0] = v.x; B[j][1] = v.y;
      }
      uint32_t fm1 = fbase[-4 * (2 * r - 1)];
#pragma unroll
      for (int k = 0; k < 16; k++) {
        const int dl = 8 * k + r;
        const uint32_t f0 = fbase[-4 * (2 * dl)];
        const uint32_t f1 = fbase[-4 * (2 * dl + 1)];
        if (k > 0) fm1 = fbase[-4 * (2 * dl - 1)];
#pragma unroll
        for (int j = k; j < 16; j++) mma_bf16(D[j], f0, f1, fm1, f0, B[j - k][0], B[j - k][1]);
      }
    }
  }
  __syncthreads();
  {
    const float dsk = __bfloat162float(Dskip[d0 + warp]);
    const bf16* uc = us + warp * USZ + UPAD;
    bf16* st = ks;
#pragma unroll
    for (int j = 0; j < 16; j++) {
#pragma unroll
      for (int q = 0; q < 4; q++) {
        const int a = 8 * j + 2 * t + (q & 1), bb = g + (q >> 1) * 8;
        const int l = 16 * a + bb;
        const int pe = ((bb & 7) >> 1) * 4 + (bb >> 3) * 2 + (bb & 1);
        const float uv = __bfloat162float(uc[16 * a + pe]);
        const float y = bfr(D[j][q]) + bfr(uv * dsk);
        st[l * 8 + ((warp + 2 * t) & 7)] = __float2bfloat16_rn(y);
      }
    }
  }
  __syncthreads();
  for (int l = tid; l < SEQ; l += 256) {
    const uint4 v = *reinterpret_cast<const uint4*>(ks + l * 8);
    const int rot = ((l >> 5) & 3);
    uint32_t w[4] = {v.x, v.y, v.z, v.w};
    uint32_t o[4];
#pragma unroll
    for (int i = 0; i < 4; i++) o[i] = rot == 0 ? w[i] : rot == 1 ? w[(i + 1) & 3] : rot == 2 ? w[(i + 2) & 3] : w[(i + 3) & 3];
    *reinterpret_cast<uint4*>(g_b + (size_t)l * DM + d0) = make_uint4(o[0], o[1], o[2], o[3]);
  }
}

typedef CUresult (*EncodeFn)(CUtensorMap*, CUtensorMapDataType, cuuint32_t, void*, const cuuint64_t*, const cuuint64_t*,
                             const cuuint32_t*, const cuuint32_t*, CUtensorMapInterleave, CUtensorMapSwizzle,
                             CUtensorMapL2promotion, CUtensorMapFloatOOBfill);

static void make_map(EncodeFn enc, CUtensorMap* m, void* ptr, uint64_t inner, uint64_t outer, uint32_t bi, uint32_t bo) {
  cuuint64_t dims[2] = {inner, outer};
  cuuint64_t strides[1] = {inner * 2};
  cuuint32_t box[2] = {bi, bo};
  cuuint32_t es[2] = {1, 1};
  enc(m, CU_TENSOR_MAP_DATA_TYPE_BFLOAT16, 2, ptr, dims, strides, box, es, CU_TENSOR_MAP_INTERLEAVE_NONE,
      CU_TENSOR_MAP_SWIZZLE_128B, CU_TENSOR_MAP_L2_PROMOTION_L2_256B, CU_TENSOR_MAP_FLOAT_OOB_FILL_NONE);
}

extern "C" void kernel_launch(void* const* d_in, const int* in_sizes, int n_in, void* d_out, int out_size) {
  const bf16* x = (const bf16*)d_in[0];
  const bf16* wqkv = (const bf16*)d_in[1];
  const bf16* wo = (const bf16*)d_in[2];
  const bf16* logAr = (const bf16*)d_in[4];
  const bf16* Aim = (const bf16*)d_in[5];
  const bf16* Cre = (const bf16*)d_in[6];
  const bf16* Cim = (const bf16*)d_in[7];
  const bf16* logdt = (const bf16*)d_in[8];
  const bf16* Dskip = (const bf16*)d_in[9];
  const bf16* gatew = (const bf16*)d_in[10];

  static EncodeFn enc = nullptr;
  static void* p_o = nullptr;
  if (!enc) {
    void* fn = nullptr;
    cudaDriverEntryPointQueryResult qr;
    cudaGetDriverEntryPoint("cuTensorMapEncodeTiled", &fn, cudaEnableDefault, &qr);
    enc = (EncodeFn)fn;
    cudaGetSymbolAddress(&p_o, g_o);
    cudaFuncSetAttribute(k1_qkv_attn, cudaFuncAttributeMaxDynamicSharedMemorySize, k1::SMEM);
    cudaFuncSetAttribute(k2_ssm, cudaFuncAttributeMaxDynamicSharedMemorySize, k2::SMEM);
    cudaFuncSetAttribute(k3_out, cudaFuncAttributeMaxDynamicSharedMemorySize, k3::SMEM);
  }
  CUtensorMap tmx, tmw, tmo, tmwo;
  make_map(enc, &tmx, (void*)x, 1024, 2048, 64, 128);
  make_map(enc, &tmw, (void*)wqkv, 3072, 1024, 64, 64);
  make_map(enc, &tmo, p_o, 1024, 2048, 64, 64);
  make_map(enc, &tmwo, (void*)wo, 1024, 1024, 64, 64);

  k2_ssm<<<128, 256, k2::SMEM>>>(x, logAr, Aim, Cre, Cim, logdt, Dskip, gatew);
  k1_qkv_attn<<<128, 384, k1::SMEM>>>(tmx, tmw);
  k3_out<<<128, 384, k3::SMEM>>>(tmo, tmwo, (bf16*)d_out);
}
```

```cpp
#include <cuda_runtime.h>
#include <cuda_bf16.h>
#include <cuda.h>
#include <stdint.h>

typedef __nv_bfloat16 bf16;

constexpr int SEQ = 2048, DM = 1024, NMODE = 128;

__device__ __align__(1024) bf16 g_o[SEQ * DM];
__device__ __align__(1024) bf16 g_b[SEQ * DM];
__device__ float g_gate[SEQ];
__device__ __align__(16) float g_part[16 * 8 * 2 * 1056];
__device__ unsigned int g_cnt[16];

__device__ __forceinline__ uint32_t smem_u32(const void* p) { return (uint32_t)__cvta_generic_to_shared(p); }
__device__ __forceinline__ void mbar_init(uint32_t bar, uint32_t cnt) {
  asm volatile("mbarrier.init.shared::cta.b64 [%0], %1;" ::"r"(bar), "r"(cnt));
}
__device__ __forceinline__ void mbar_expect_tx(uint32_t bar, uint32_t bytes) {
  asm volatile("mbarrier.arrive.expect_tx.shared::cta.b64 _, [%0], %1;" ::"r"(bar), "r"(bytes) : "memory");
}
__device__ __forceinline__ void mbar_arrive_cluster(uint32_t bar, uint32_t cta) {
  asm volatile(
      "{\n.reg .b32 ra;\nmapa.shared::cluster.u32 ra, %0, %1;\n"
      "mbarrier.arrive.shared::cluster.b64 _, [ra];\n}\n" ::"r"(bar), "r"(cta) : "memory");
}
__device__ __forceinline__ bool mbar_try_wait(uint32_t bar, uint32_t parity) {
  uint32_t ok;
  asm volatile(
      "{\n.reg .pred p;\nmbarrier.try_wait.parity.shared::cta.b64 p, [%1], %2;\nselp.u32 %0, 1, 0, p;\n}\n"
      : "=r"(ok) : "r"(bar), "r"(parity) : "memory");
  return ok;
}
__device__ __forceinline__ void mbar_wait(uint32_t bar, uint32_t parity) {
  while (!mbar_try_wait(bar, parity)) {}
}
__device__ __forceinline__ void tma_load_2d(uint32_t dst, const CUtensorMap* map, uint32_t bar, int c0, int c1) {
  asm volatile(
      "cp.async.bulk.tensor.2d.shared::cluster.global.mbarrier::complete_tx::bytes [%0], [%1, {%3, %4}], [%2];" ::"r"(dst),
      "l"(map), "r"(bar), "r"(c0), "r"(c1) : "memory");
}
__device__ __forceinline__ void tma_load_2d_mc(uint32_t dst, const CUtensorMap* map, uint32_t bar, int c0, int c1,
                                               uint16_t mask) {
  asm volatile(
      "cp.async.bulk.tensor.2d.shared::cluster.global.mbarrier::complete_tx::bytes.multicast::cluster [%0], [%1, {%3, %4}], [%2], %5;" ::"r"(dst),
      "l"(map), "r"(bar), "r"(c0), "r"(c1), "h"(mask) : "memory");
}
__device__ __forceinline__ void cluster_sync_all() {
  asm volatile("barrier.cluster.arrive.release.aligned;\nbarrier.cluster.wait.acquire.aligned;\n" ::: "memory");
}
__device__ __forceinline__ uint32_t cluster_ctarank() {
  uint32_t r; asm volatile("mov.u32 %0, %%cluster_ctarank;" : "=r"(r)); return r;
}
__device__ __forceinline__ void named_bar_sync(int id, int n) { asm volatile("bar.sync %0, %1;" ::"r"(id), "r"(n) : "memory"); }
__device__ __forceinline__ void fence_async_smem() { asm volatile("fence.proxy.async.shared::cta;" ::: "memory"); }
__device__ __forceinline__ void wg_fence() { asm volatile("wgmma.fence.sync.aligned;" ::: "memory"); }
__device__ __forceinline__ void wg_commit() { asm volatile("wgmma.commit_group.sync.aligned;" ::: "memory"); }
template <int N> __device__ __forceinline__ void wg_wait() { asm volatile("wgmma.wait_group.sync.aligned %0;" ::"n"(N) : "memory"); }
__device__ __forceinline__ uint64_t make_desc(uint32_t addr, uint32_t lbo, uint32_t sbo) {
  return (uint64_t)((addr & 0x3FFFF) >> 4) | ((uint64_t)(lbo >> 4) << 16) | ((uint64_t)(sbo >> 4) << 32) | (1ull << 62);
}
__device__ __forceinline__ float bfr(float x) { return __bfloat162float(__float2bfloat16_rn(x)); }
__device__ __forceinline__ uint32_t pack2(float lo, float hi) {
  __nv_bfloat162 v = __floats2bfloat162_rn(lo, hi);
  return *reinterpret_cast<uint32_t*>(&v);
}
__device__ __forceinline__ float ex2f(float x) { float r; asm("ex2.approx.ftz.f32 %0, %1;" : "=f"(r) : "f"(x)); return r; }
__device__ __forceinline__ float lo_f(uint32_t v) { return __uint_as_float(v << 16); }
__device__ __forceinline__ float hi_f(uint32_t v) { return __uint_as_float(v & 0xffff0000u); }
__device__ __forceinline__ uint32_t phi2(float a0, float a1) {
  const uint32_t t2 = pack2(a0, a1);
  const float t0 = lo_f(t2), t1 = hi_f(t2);
  const float e0 = ex2f(t0 * 1.4426950408889634f), e1 = ex2f(t1 * 1.4426950408889634f);
  const float f0 = t0 > 0.f ? t0 + 1.0f : e0;
  const float f1 = t1 > 0.f ? t1 + 1.0f : e1;
  const uint32_t f2 = pack2(f0, f1);
  return pack2(lo_f(f2) + 1e-6f, hi_f(f2) + 1e-6f);
}
template <int R> __device__ __forceinline__ void fence_regs(float (&d)[R]) {
#pragma unroll
  for (int i = 0; i < R; i++) asm volatile("" : "+f"(d[i])::"memory");
}

__device__ __forceinline__ void wgmma_ss_n192_tb(float (&d)[96], uint64_t da, uint64_t db, int sc) {
  asm volatile("{\n.reg .pred p;\nsetp.ne.b32 p, %98, 0;\n"
    "wgmma.mma_async.sync.aligned.m64n192k16.f32.bf16.bf16 {%0, %1, %2, %3, %4, %5, %6, %7, %8, %9, %10, %11, %12, %13, %14, %15, %16, %17, %18, %19, %20, %21, %22, %23, %24, %25, %26, %27, %28, %29, %30, %31, %32, %33, %34, %35, %36, %37, %38, %39, %40, %41, %42, %43, %44, %45, %46, %47, %48, %49, %50, %51, %52, %53, %54, %55, %56, %57, %58, %59, %60, %61, %62, %63, %64, %65, %66, %67, %68, %69, %70, %71, %72, %73, %74, %75, %76, %77, %78, %79, %80, %81, %82, %83, %84, %85, %86, %87, %88, %89, %90, %91, %92, %93, %94, %95}, %96, %97, p, 1, 1, 0, 1;\n}\n"
    : "+f"(d[0]), "+f"(d[1]), "+f"(d[2]), "+f"(d[3]), "+f"(d[4]), "+f"(d[5]), "+f"(d[6]), "+f"(d[7]), "+f"(d[8]), "+f"(d[9]), "+f"(d[10]), "+f"(d[11]), "+f"(d[12]), "+f"(d[13]), "+f"(d[14]), "+f"(d[15]), "+f"(d[16]), "+f"(d[17]), "+f"(d[18]), "+f"(d[19]), "+f"(d[20]), "+f"(d[21]), "+f"(d[22]), "+f"(d[23]), "+f"(d[24]), "+f"(d[25]), "+f"(d[26]), "+f"(d[27]), "+f"(d[28]), "+f"(d[29]), "+f"(d[30]), "+f"(d[31]), "+f"(d[32]), "+f"(d[33]), "+f"(d[34]), "+f"(d[35]), "+f"(d[36]), "+f"(d[37]), "+f"(d[38]), "+f"(d[39]), "+f"(d[40]), "+f"(d[41]), "+f"(d[42]), "+f"(d[43]), "+f"(d[44]), "+f"(d[45]), "+f"(d[46]), "+f"(d[47]), "+f"(d[48]), "+f"(d[49]), "+f"(d[50]), "+f"(d[51]), "+f"(d[52]), "+f"(d[53]), "+f"(d[54]), "+f"(d[55]), "+f"(d[56]), "+f"(d[57]), "+f"(d[58]), "+f"(d[59]), "+f"(d[60]), "+f"(d[61]), "+f"(d[62]), "+f"(d[63]), "+f"(d[64]), "+f"(d[65]), "+f"(d[66]), "+f"(d[67]), "+f"(d[68]), "+f"(d[69]), "+f"(d[70]), "+f"(d[71]), "+f"(d[72]), "+f"(d[73]), "+f"(d[74]), "+f"(d[75]), "+f"(d[76]), "+f"(d[77]), "+f"(d[78]), "+f"(d[79]), "+f"(d[80]), "+f"(d[81]), "+f"(d[82]), "+f"(d[83]), "+f"(d[84]), "+f"(d[85]), "+f"(d[86]), "+f"(d[87]), "+f"(d[88]), "+f"(d[89]), "+f"(d[90]), "+f"(d[91]), "+f"(d[92]), "+f"(d[93]), "+f"(d[94]), "+f"(d[95])
    : "l"(da), "l"(db), "r"(sc));
}

__device__ __forceinline__ void wgmma_ss_n128_tb(float (&d)[64], uint64_t da, uint64_t db, int sc) {
  asm volatile("{\n.reg .pred p;\nsetp.ne.b32 p, %66, 0;\n"
    "wgmma.mma_async.sync.aligned.m64n128k16.f32.bf16.bf16 {%0, %1, %2, %3, %4, %5, %6, %7, %8, %9, %10, %11, %12, %13, %14, %15, %16, %17, %18, %19, %20, %21, %22, %23, %24, %25, %26, %27, %28, %29, %30, %31, %32, %33, %34, %35, %36, %37, %38, %39, %40, %41, %42, %43, %44, %45, %46, %47, %48, %49, %50, %51, %52, %53, %54, %55, %56, %57, %58, %59, %60, %61, %62, %63}, %64, %65, p, 1, 1, 0, 1;\n}\n"
    : "+f"(d[0]), "+f"(d[1]), "+f"(d[2]), "+f"(d[3]), "+f"(d[4]), "+f"(d[5]), "+f"(d[6]), "+f"(d[7]), "+f"(d[8]), "+f"(d[9]), "+f"(d[10]), "+f"(d[11]), "+f"(d[12]), "+f"(d[13]), "+f"(d[14]), "+f"(d[15]), "+f"(d[16]), "+f"(d[17]), "+f"(d[18]), "+f"(d[19]), "+f"(d[20]), "+f"(d[21]), "+f"(d[22]), "+f"(d[23]), "+f"(d[24]), "+f"(d[25]), "+f"(d[26]), "+f"(d[27]), "+f"(d[28]), "+f"(d[29]), "+f"(d[30]), "+f"(d[31]), "+f"(d[32]), "+f"(d[33]), "+f"(d[34]), "+f"(d[35]), "+f"(d[36]), "+f"(d[37]), "+f"(d[38]), "+f"(d[39]), "+f"(d[40]), "+f"(d[41]), "+f"(d[42]), "+f"(d[43]), "+f"(d[44]), "+f"(d[45]), "+f"(d[46]), "+f"(d[47]), "+f"(d[48]), "+f"(d[49]), "+f"(d[50]), "+f"(d[51]), "+f"(d[52]), "+f"(d[53]), "+f"(d[54]), "+f"(d[55]), "+f"(d[56]), "+f"(d[57]), "+f"(d[58]), "+f"(d[59]), "+f"(d[60]), "+f"(d[61]), "+f"(d[62]), "+f"(d[63])
    : "l"(da), "l"(db), "r"(sc));
}

__device__ __forceinline__ void wgmma_ss_n64_tatb(float (&d)[32], uint64_t da, uint64_t db, int sc) {
  asm volatile("{\n.reg .pred p;\nsetp.ne.b32 p, %34, 0;\n"
    "wgmma.mma_async.sync.aligned.m64n64k16.f32.bf16.bf16 {%0, %1, %2, %3, %4, %5, %6, %7, %8, %9, %10, %11, %12, %13, %14, %15, %16, %17, %18, %19, %20, %21, %22, %23, %24, %25, %26, %27, %28, %29, %30, %31}, %32, %33, p, 1, 1, 1, 1;\n}\n"
    : "+f"(d[0]), "+f"(d[1]), "+f"(d[2]), "+f"(d[3]), "+f"(d[4]), "+f"(d[5]), "+f"(d[6]), "+f"(d[7]), "+f"(d[8]), "+f"(d[9]), "+f"(d[10]), "+f"(d[11]), "+f"(d[12]), "+f"(d[13]), "+f"(d[14]), "+f"(d[15]), "+f"(d[16]), "+f"(d[17]), "+f"(d[18]), "+f"(d[19]), "+f"(d[20]), "+f"(d[21]), "+f"(d[22]), "+f"(d[23]), "+f"(d[24]), "+f"(d[25]), "+f"(d[26]), "+f"(d[27]), "+f"(d[28]), "+f"(d[29]), "+f"(d[30]), "+f"(d[31])
    : "l"(da), "l"(db), "r"(sc));
}

__device__ __forceinline__ void wgmma_ss_n8_tatb(float (&d)[4], uint64_t da, uint64_t db, int sc) {
  asm volatile("{\n.reg .pred p;\nsetp.ne.b32 p, %6, 0;\n"
    "wgmma.mma_async.sync.aligned.m64n8k16.f32.bf16.bf16 {%0, %1, %2, %3}, %4, %5, p, 1, 1, 1, 1;\n}\n"
    : "+f"(d[0]), "+f"(d[1]), "+f"(d[2]), "+f"(d[3])
    : "l"(da), "l"(db), "r"(sc));
}

__device__ __forceinline__ void wgmma_rs_n40_tb(float (&d)[20], uint32_t a0, uint32_t a1, uint32_t a2, uint32_t a3, uint64_t db, int sc) {
  asm volatile("{\n.reg .pred p;\nsetp.ne.b32 p, %25, 0;\n"
    "wgmma.mma_async.sync.aligned.m64n40k16.f32.bf16.bf16 {%0, %1, %2, %3, %4, %5, %6, %7, %8, %9, %10, %11, %12, %13, %14, %15, %16, %17, %18, %19}, {%20, %21, %22, %23}, %24, p, 1, 1, 1;\n}\n"
    : "+f"(d[0]), "+f"(d[1]), "+f"(d[2]), "+f"(d[3]), "+f"(d[4]), "+f"(d[5]), "+f"(d[6]), "+f"(d[7]), "+f"(d[8]), "+f"(d[9]), "+f"(d[10]), "+f"(d[11]), "+f"(d[12]), "+f"(d[13]), "+f"(d[14]), "+f"(d[15]), "+f"(d[16]), "+f"(d[17]), "+f"(d[18]), "+f"(d[19])
    : "r"(a0), "r"(a1), "r"(a2), "r"(a3), "l"(db), "r"(sc));
}


namespace k1 {
constexpr int BM = 256, BN = 192, BK = 64, ST = 4;
constexpr int A_BYTES = BM * BK * 2, B_BYTES = BK * BN * 2, STAGE = A_BYTES + B_BYTES;
constexpr int SMEM = ST * STAGE + 1024 + 256;
constexpr int OFF_PK = 0, OFF_V = 32768, OFF_ONES = 65536, OFF_KV = 69632, OFF_O = 81920, OFF_RED = 114688;
}

__global__ void __cluster_dims__(2, 1, 1) __launch_bounds__(384, 1)
k1_qkv_attn(const __grid_constant__ CUtensorMap tmx, const __grid_constant__ CUtensorMap tmw) {
  using namespace k1;
  extern __shared__ uint8_t smem_raw[];
  const uint32_t sbase = (smem_u32(smem_raw) + 1023) & ~1023u;
  uint8_t* sgen = smem_raw + (sbase - smem_u32(smem_raw));
  const uint32_t bars = sbase + ST * STAGE;
  const int tid = threadIdx.x, warp = tid >> 5, lane = tid & 31;
  const uint32_t rank = cluster_ctarank();
  const int cl = blockIdx.x >> 1;
  const int mt = cl >> 3;
  const int hp = ((cl & 7) << 1) + rank;
  const int m0 = mt * BM;

  if (tid == 0) {
    for (int s = 0; s < ST; s++) {
      mbar_init(bars + 8 * s, 1);
      mbar_init(bars + 8 * (ST + s), 16);
    }
    asm volatile("fence.mbarrier_init.release.cluster;" ::: "memory");
  }
  cluster_sync_all();

  if (warp >= 8) {
    asm volatile("setmaxnreg.dec.sync.aligned.u32 40;");
    if (warp == 8 && lane == 0) {
      for (int kb = 0; kb < DM / BK; kb++) {
        const int s = kb % ST;
        mbar_wait(bars + 8 * (ST + s), ((kb / ST) & 1) ^ 1);
        const uint32_t full = bars + 8 * s;
        mbar_expect_tx(full, STAGE);
        const uint32_t sa = sbase + s * STAGE, sb = sa + A_BYTES;
        tma_load_2d_mc(sa + rank * 16384, &tmx, full, kb * BK, m0 + rank * 128, (uint16_t)3);
#pragma unroll
        for (int j = 0; j < 3; j++) tma_load_2d(sb + j * 8192, &tmw, full, j * 1024 + hp * 64, kb * BK);
      }
    }
    cluster_sync_all();
  } else {
    asm volatile("setmaxnreg.inc.sync.aligned.u32 232;");
    const int wg = warp >> 2, w4 = warp & 3, g = lane >> 2, t = lane & 3;
    float acc[2][96];
#pragma unroll
    for (int i = 0; i < 96; i++) { acc[0][i] = 0.f; acc[1][i] = 0.f; }
    for (int kb = 0; kb < DM / BK; kb++) {
      const int s = kb % ST;
      mbar_wait(bars + 8 * s, (kb / ST) & 1);
      const uint32_t sa = sbase + s * STAGE + wg * 16384, sb = sbase + s * STAGE + A_BYTES;
      wg_fence();
#pragma unroll
      for (int ks = 0; ks < 4; ks++) {
        const uint64_t db = make_desc(sb + ks * 2048, 8192, 1024);
#pragma unroll
        for (int mb = 0; mb < 2; mb++) {
          const uint64_t da = make_desc(sa + mb * 8192 + ks * 32, 16, 1024);
          wgmma_ss_n192_tb(acc[mb], da, db, 1);
        }
      }
      wg_commit();
      if (kb > 0) {
        wg_wait<1>();
        const int sp = (kb - 1) % ST;
        if (lane == 0) { mbar_arrive_cluster(bars + 8 * (ST + sp), 0); mbar_arrive_cluster(bars + 8 * (ST + sp), 1); }
      }
    }
    wg_wait<0>();
    fence_regs(acc[0]); fence_regs(acc[1]);
    named_bar_sync(1, 256);

#pragma unroll
    for (int mb = 0; mb < 2; mb++) {
#pragma unroll
      for (int h = 0; h < 2; h++) {
        const int r = wg * 128 + mb * 64 + w4 * 16 + g + h * 8;
#pragma unroll
        for (int j = 0; j < 8; j++) {
          const uint32_t off = r * 128 + ((j ^ (r & 7)) << 4) + t * 4;
          const float k0 = acc[mb][4 * (8 + j) + 2 * h], k1v = acc[mb][4 * (8 + j) + 2 * h + 1];
          const float v0 = acc[mb][4 * (16 + j) + 2 * h], v1 = acc[mb][4 * (16 + j) + 2 * h + 1];
          *reinterpret_cast<uint32_t*>(sgen + OFF_PK + off) = phi2(k0, k1v);
          *reinterpret_cast<uint32_t*>(sgen + OFF_V + off) = pack2(v0, v1);
        }
      }
    }
    if (tid < 256) *reinterpret_cast<uint32_t*>(sgen + OFF_ONES + tid * 4) = 0x3F803F80u;
    fence_async_smem();
    named_bar_sync(1, 256);

    float* part = g_part + (size_t)(hp * 8 + mt) * 2112;
    {
      float kv[32], zz[4];
#pragma unroll
      for (int i = 0; i < 32; i++) kv[i] = 0.f;
#pragma unroll
      for (int i = 0; i < 4; i++) zz[i] = 0.f;
      wg_fence();
#pragma unroll
      for (int ks = 0; ks < 8; ks++) {
        const uint64_t da = make_desc(sbase + OFF_PK + wg * 16384 + ks * 2048, 16, 1024);
        const uint64_t db = make_desc(sbase + OFF_V + wg * 16384 + ks * 2048, 16, 1024);
        const uint64_t d1 = make_desc(sbase + OFF_ONES, 16, 0);
        wgmma_ss_n64_tatb(kv, da, db, 1);
        wgmma_ss_n8_tatb(zz, da, d1, 1);
      }
      wg_commit();
      wg_wait<0>();
      fence_regs(kv); fence_regs(zz);
      const int hh = w4 >> 1;
      float* red = reinterpret_cast<float*>(sgen + OFF_RED);
      float vals[2][4][2];
#pragma unroll
      for (int h = 0; h < 2; h++)
#pragma unroll
        for (int j = 0; j < 4; j++) {
          vals[h][j][0] = hh ? kv[4 * (4 + j) + 2 * h] : kv[4 * j + 2 * h];
          vals[h][j][1] = hh ? kv[4 * (4 + j) + 2 * h + 1] : kv[4 * j + 2 * h + 1];
        }
      if (wg == 1) {
#pragma unroll
        for (int h = 0; h < 2; h++) {
          const int d = (w4 & 1) * 16 + g + h * 8;
#pragma unroll
          for (int j = 0; j < 4; j++)
            *reinterpret_cast<float2*>(red + hh * 1056 + d * 32 + 8 * j + 2 * t) = make_float2(vals[h][j][0], vals[h][j][1]);
          if (t == 0) red[hh * 1056 + 1024 + d] = zz[2 * h];
        }
      }
      named_bar_sync(1, 256);
      if (wg == 0) {
#pragma unroll
        for (int h = 0; h < 2; h++) {
          const int d = (w4 & 1) * 16 + g + h * 8;
#pragma unroll
          for (int j = 0; j < 4; j++) {
            const float2 o = *reinterpret_cast<const float2*>(red + hh * 1056 + d * 32 + 8 * j + 2 * t);
            *reinterpret_cast<float2*>(part + hh * 1056 + d * 32 + 8 * j + 2 * t) = make_float2(vals[h][j][0] + o.x, vals[h][j][1] + o.y);
          }
          if (t == 0) part[hh * 1056 + 1024 + d] = zz[2 * h] + red[hh * 1056 + 1024 + d];
        }
        __threadfence();
        named_bar_sync(2, 128);
        if (tid == 0) atomicAdd(&g_cnt[hp], 1u);
      }
    }
    uint32_t pq[2][4][4];
#pragma unroll
    for (int mb = 0; mb < 2; mb++)
#pragma unroll
      for (int kk = 0; kk < 4; kk++) {
        pq[mb][kk][0] = phi2(acc[mb][8 * kk + 0], acc[mb][8 * kk + 1]);
        pq[mb][kk][1] = phi2(acc[mb][8 * kk + 2], acc[mb][8 * kk + 3]);
        pq[mb][kk][2] = phi2(acc[mb][8 * kk + 4], acc[mb][8 * kk + 5]);
        pq[mb][kk][3] = phi2(acc[mb][8 * kk + 6], acc[mb][8 * kk + 7]);
      }
    if (tid == 0) {
      unsigned int v;
      do { asm volatile("ld.acquire.gpu.global.u32 %0, [%1];" : "=r"(v) : "l"(&g_cnt[hp]) : "memory"); } while (v < 8u);
    }
    named_bar_sync(1, 256);
    {
      const float* pb = g_part + (size_t)(hp * 8) * 2112;
      for (int i = tid; i < 528; i += 256) {
        float4 s4 = make_float4(0.f, 0.f, 0.f, 0.f);
#pragma unroll
        for (int p = 0; p < 8; p++) {
          float4 v4 = __ldcg(reinterpret_cast<const float4*>(pb + p * 2112) + i);
          s4.x += v4.x; s4.y += v4.y; s4.z += v4.z; s4.w += v4.w;
        }
        const int hh = i / 264, rem = i - hh * 264;
        uint8_t* tile = sgen + OFF_KV + hh * 4096;
        if (rem < 256) {
          const int d = rem >> 3, e = (rem & 7) * 4;
          const uint32_t off = d * 128 + (((e >> 3) ^ (d & 7)) << 4) + (e & 7) * 2;
          *reinterpret_cast<uint2*>(tile + off) = make_uint2(pack2(s4.x, s4.y), pack2(s4.z, s4.w));
        } else {
          const int d0 = (rem - 256) * 4;
          float zv[4] = {s4.x, s4.y, s4.z, s4.w};
#pragma unroll
          for (int q = 0; q < 4; q++) {
            const int d = d0 + q;
            const uint32_t off = d * 128 + ((4 ^ (d & 7)) << 4);
            *reinterpret_cast<uint4*>(tile + off) = make_uint4(pack2(zv[q], 0.f), 0u, 0u, 0u);
          }
        }
      }
    }
    fence_async_smem();
    named_bar_sync(1, 256);
#pragma unroll
    for (int mb = 0; mb < 2; mb++) {
#pragma unroll
      for (int hh = 0; hh < 2; hh++) {
        float num[20];
#pragma unroll
        for (int i = 0; i < 20; i++) num[i] = 0.f;
        wg_fence();
#pragma unroll
        for (int kk = 0; kk < 2; kk++) {
          const uint64_t db = make_desc(sbase + OFF_KV + hh * 4096 + kk * 2048, 16, 1024);
          wgmma_rs_n40_tb(num, pq[mb][hh * 2 + kk][0], pq[mb][hh * 2 + kk][1], pq[mb][hh * 2 + kk][2], pq[mb][hh * 2 + kk][3], db, 1);
        }
        wg_commit();
        wg_wait<0>();
        fence_regs(num);
#pragma unroll
        for (int h = 0; h < 2; h++) {
          float den = __shfl_sync(0xffffffffu, num[16 + 2 * h], lane & ~3);
          den = bfr(bfr(den) + 1e-6f);
          const float rden = 1.0f / den;
          const int r = wg * 128 + mb * 64 + w4 * 16 + g + h * 8;
#pragma unroll
          for (int j = 0; j < 4; j++) {
            const uint32_t n2 = pack2(num[4 * j + 2 * h], num[4 * j + 2 * h + 1]);
            const float o0 = lo_f(n2) * rden, o1 = hi_f(n2) * rden;
            const uint32_t off = r * 128 + (((hh * 4 + j) ^ (r & 7)) << 4) + t * 4;
            *reinterpret_cast<uint32_t*>(sgen + OFF_O + off) = pack2(o0, o1);
          }
        }
      }
    }
    named_bar_sync(1, 256);
    for (int i = tid; i < 256 * 8; i += 256) {
      const int r = i >> 3, c = i & 7;
      uint4 v = *reinterpret_cast<const uint4*>(sgen + OFF_O + r * 128 + ((c ^ (r & 7)) << 4));
      *reinterpret_cast<uint4*>(g_o + (size_t)(m0 + r) * DM + hp * 64 + c * 8) = v;
    }
    cluster_sync_all();
  }
}

namespace k3 {
constexpr int BM = 128, BN = 128, BK = 64, ST = 6;
constexpr int A_BYTES = BM * BK * 2, B_BYTES = BK * BN * 2, STAGE = A_BYTES + B_BYTES;
constexpr int SMEM = ST * STAGE + 1024 + 256;
}

__global__ void __cluster_dims__(2, 1, 1) __launch_bounds__(384, 1)
k3_out(const __grid_constant__ CUtensorMap tmo, const __grid_constant__ CUtensorMap tmw, bf16* __restrict__ out) {
  using namespace k3;
  extern __shared__ uint8_t smem_raw[];
  const uint32_t sbase = (smem_u32(smem_raw) + 1023) & ~1023u;
  const uint32_t bars = sbase + ST * STAGE;
  const int tid = threadIdx.x, warp = tid >> 5, lane = tid & 31;
  const uint32_t rank = cluster_ctarank();
  const int cl = blockIdx.x >> 1;
  const int mt = cl >> 2;
  const int nt = ((cl & 3) << 1) + rank;
  const int m0 = mt * BM, n0 = nt * BN;
  if (blockIdx.x == 0 && tid < 16) g_cnt[tid] = 0;

  if (tid == 0) {
    for (int s = 0; s < ST; s++) {
      mbar_init(bars + 8 * s, 1);
      mbar_init(bars + 8 * (ST + s), 16);
    }
    asm volatile("fence.mbarrier_init.release.cluster;" ::: "memory");
  }
  cluster_sync_all();

  if (warp >= 8) {
    asm volatile("setmaxnreg.dec.sync.aligned.u32 40;");
    if (warp == 8 && lane == 0) {
      for (int kb = 0; kb < DM / BK; kb++) {
        const int s = kb % ST;
        mbar_wait(bars + 8 * (ST + s), ((kb / ST) & 1) ^ 1);
        const uint32_t full = bars + 8 * s;
        mbar_expect_tx(full, STAGE);
        const uint32_t sa = sbase + s * STAGE, sb = sa + A_BYTES;
        tma_load_2d_mc(sa + rank * 8192, &tmo, full, kb * BK, m0 + rank * 64, (uint16_t)3);
#pragma unroll
        for (int j = 0; j < 2; j++) tma_load_2d(sb + j * 8192, &tmw, full, n0 + j * 64, kb * BK);
      }
    }
    cluster_sync_all();
  } else {
    asm volatile("setmaxnreg.inc.sync.aligned.u32 232;");
    const int wg = warp >> 2, w4 = warp & 3, g = lane >> 2, t = lane & 3;
    float acc[64];
#pragma unroll
    for (int i = 0; i < 64; i++) acc[i] = 0.f;
    for (int kb = 0; kb < DM / BK; kb++) {
      const int s = kb % ST;
      mbar_wait(bars + 8 * s, (kb / ST) & 1);
      const uint32_t sa = sbase + s * STAGE + wg * 8192, sb = sbase + s * STAGE + A_BYTES;
      wg_fence();
#pragma unroll
      for (int ks = 0; ks < 4; ks++) {
        const uint64_t db = make_desc(sb + ks * 2048, 8192, 1024);
        const uint64_t da = make_desc(sa + ks * 32, 16, 1024);
        wgmma_ss_n128_tb(acc, da, db, 1);
      }
      wg_commit();
      if (kb > 0) {
        wg_wait<1>();
        const int sp = (kb - 1) % ST;
        if (lane == 0) { mbar_arrive_cluster(bars + 8 * (ST + sp), 0); mbar_arrive_cluster(bars + 8 * (ST + sp), 1); }
      }
    }
    wg_wait<0>();
    fence_regs(acc);
#pragma unroll
    for (int h = 0; h < 2; h++) {
      const int r = m0 + wg * 64 + w4 * 16 + g + h * 8;
      const float gt = g_gate[r];
      const float omg = bfr(1.0f - gt);
#pragma unroll
      for (int j = 0; j < 16; j++) {
        const int c = n0 + 8 * j + 2 * t;
        const __nv_bfloat162 bb = *reinterpret_cast<const __nv_bfloat162*>(g_b + (size_t)r * DM + c);
        const float o0 = bfr(gt * bfr(acc[4 * j + 2 * h])) + bfr(omg * __bfloat162float(bb.x));
        const float o1 = bfr(gt * bfr(acc[4 * j + 2 * h + 1])) + bfr(omg * __bfloat162float(bb.y));
        *reinterpret_cast<uint32_t*>(out + (size_t)r * DM + c) = pack2(o0, o1);
      }
    }
    cluster_sync_all();
  }
}

__device__ float g_kq[DM * 648];

__device__ __forceinline__ void mma_bf16(float (&d)[4], uint32_t a0, uint32_t a1, uint32_t a2, uint32_t a3, uint32_t b0, uint32_t b1) {
  asm volatile("mma.sync.aligned.m16n8k16.row.col.f32.bf16.bf16.f32 {%0,%1,%2,%3}, {%4,%5,%6,%7}, {%8,%9}, {%0,%1,%2,%3};"
               : "+f"(d[0]), "+f"(d[1]), "+f"(d[2]), "+f"(d[3]) : "r"(a0), "r"(a1), "r"(a2), "r"(a3), "r"(b0), "r"(b1));
}
__device__ __forceinline__ void mma_tf32(float (&d)[4], uint32_t a0, uint32_t a1, uint32_t a2, uint32_t a3, uint32_t b0, uint32_t b1) {
  asm volatile("mma.sync.aligned.m16n8k8.row.col.f32.tf32.tf32.f32 {%0,%1,%2,%3}, {%4,%5,%6,%7}, {%8,%9}, {%0,%1,%2,%3};"
               : "+f"(d[0]), "+f"(d[1]), "+f"(d[2]), "+f"(d[3]) : "r"(a0), "r"(a1), "r"(a2), "r"(a3), "r"(b0), "r"(b1));
}
__device__ __forceinline__ uint32_t tf32r(float x) { uint32_t r; asm("cvt.rna.tf32.f32 %0, %1;" : "=r"(r) : "f"(x)); return r; }
struct cf { float r, i; };
__device__ __forceinline__ cf cmul(cf a, cf b) { cf c; c.r = a.r * b.r - a.i * b.i; c.i = a.r * b.i + a.i * b.r; return c; }
__device__ __forceinline__ cf csq(cf a) { cf c; c.r = a.r * a.r - a.i * a.i; c.i = 2.f * a.r * a.i; return c; }
__device__ __forceinline__ cf cexpp(float ar, float ai, float p) {
  const float e = ex2f(ar * p * 1.4426950408889634f);
  const float th = ai * p;
  const float k = rintf(th * 0.15915494309189535f);
  float r = fmaf(k, -6.2831854820251465f, th);
  r = fmaf(k, 1.7484556000744e-7f, r);
  cf w; w.r = e * __cosf(r); w.i = e * __sinf(r); return w;
}

__device__ __forceinline__ void kgen_channel(int d, int lane, const bf16* __restrict__ logAr, const bf16* __restrict__ Aim,
                                             const bf16* __restrict__ Cre, const bf16* __restrict__ Cim,
                                             const bf16* __restrict__ logdt) {
  const int g = lane >> 2, t = lane & 3;
  const float dt = bfr(ex2f(__bfloat162float(logdt[d]) * 1.4426950408889634f));
  float acc[5][4];
#pragma unroll
  for (int a = 0; a < 5; a++)
#pragma unroll
    for (int b = 0; b < 4; b++) acc[a][b] = 0.f;
  float last = 0.f;
#pragma unroll 2
  for (int n0 = 0; n0 < NMODE; n0 += 4) {
    const int idx = d * NMODE + n0 + t;
    const float ar = -bfr(ex2f(__bfloat162float(logAr[idx]) * 1.4426950408889634f)) * dt;
    const float ai = __bfloat162float(Aim[idx]) * dt;
    cf C; C.r = __bfloat162float(Cre[idx]) * dt; C.i = __bfloat162float(Cim[idx]) * dt;
    const cf Y1 = cexpp(ar, ai, (float)g);
    const cf Y8 = cexpp(ar, ai, (float)(8 * g));
    const cf W64 = cexpp(ar, ai, 64.f);
    const cf Y2 = csq(Y1), Y4 = csq(Y2);
    const cf Y16 = csq(Y8), Y32 = csq(Y16), Y64 = csq(Y32);
    const cf W128 = csq(W64), W256 = csq(W128), W512 = csq(W256), W1024 = csq(W512);
    const cf X0a = cmul(C, Y8), X0b = cmul(X0a, W64);
    const cf X1a = cmul(X0a, W128), X1b = cmul(X0b, W128);
    const cf X2a = cmul(cmul(C, W256), Y16), X2b = cmul(X2a, W128);
    const cf X3a = cmul(cmul(C, W512), Y32), X3b = cmul(X3a, W256);
    const cf C4 = cmul(C, W1024);
    const cf X4a = cmul(C4, Y64), X4b = cmul(X4a, W512);
    last += C4.r * W1024.r - C4.i * W1024.i;
    const uint32_t y1r = tf32r(Y1.r), y1i = tf32r(Y1.i);
    mma_tf32(acc[0], tf32r(X0a.r), tf32r(X0b.r), tf32r(-X0a.i), tf32r(-X0b.i), y1r, y1i);
    mma_tf32(acc[1], tf32r(X1a.r), tf32r(X1b.r), tf32r(-X1a.i), tf32r(-X1b.i), y1r, y1i);
    mma_tf32(acc[2], tf32r(X2a.r), tf32r(X2b.r), tf32r(-X2a.i), tf32r(-X2b.i), tf32r(Y2.r), tf32r(Y2.i));
    mma_tf32(acc[3], tf32r(X3a.r), tf32r(X3b.r), tf32r(-X3a.i), tf32r(-X3b.i), tf32r(Y4.r), tf32r(Y4.i));
    mma_tf32(acc[4], tf32r(X4a.r), tf32r(X4b.r), tf32r(-X4a.i), tf32r(-X4b.i), tf32r(Y8.r), tf32r(Y8.i));
  }
  float* kq = g_kq + d * 648;
#pragma unroll
  for (int a = 0; a < 5; a++) {
    *reinterpret_cast<float2*>(kq + 128 * a + 8 * g + 2 * t) = make_float2(2.f * acc[a][0], 2.f * acc[a][1]);
    *reinterpret_cast<float2*>(kq + 128 * a + 8 * (g + 8) + 2 * t) = make_float2(2.f * acc[a][2], 2.f * acc[a][3]);
  }
  last += __shfl_xor_sync(0xffffffffu, last, 1);
  last += __shfl_xor_sync(0xffffffffu, last, 2);
  if (lane == 0) kq[640] = 2.f * last;
}

__global__ void __launch_bounds__(256)
k0_kgen(const bf16* __restrict__ x, const bf16* __restrict__ logAr, const bf16* __restrict__ Aim, const bf16* __restrict__ Cre,
        const bf16* __restrict__ Cim, const bf16* __restrict__ logdt, const bf16* __restrict__ gatew) {
  const int warp = threadIdx.x >> 5, lane = threadIdx.x & 31;
  for (int rr = 0; rr < 2; rr++) {
    const int r = blockIdx.x * 16 + warp * 2 + rr;
    float s = 0.f;
    for (int c = lane * 8; c < DM; c += 256) {
      uint4 xv = *reinterpret_cast<const uint4*>(x + (size_t)r * DM + c);
      uint4 wv = *reinterpret_cast<const uint4*>(gatew + c);
      const bf16* xp = reinterpret_cast<const bf16*>(&xv);
      const bf16* wp = reinterpret_cast<const bf16*>(&wv);
#pragma unroll
      for (int q = 0; q < 8; q++) s += bfr(__bfloat162float(xp[q]) * __bfloat162float(wp[q]));
    }
#pragma unroll
    for (int o = 16; o; o >>= 1) s += __shfl_xor_sync(0xffffffffu, s, o);
    if (lane == 0) { float z = bfr(s); g_gate[r] = bfr(1.0f / (1.0f + expf(-z))); }
  }
  kgen_channel(blockIdx.x * 8 + warp, lane, logAr, Aim, Cre, Cim, logdt);
}

namespace k2 {
constexpr int CH = 8;
constexpr int UPAD = 128;
constexpr int USZ = UPAD + SEQ;
constexpr int KOFF = 2048 + 16;
constexpr int KSZ = 2112;
constexpr int KCH = 2 * KSZ + 16;
constexpr int OFF_U = 0;
constexpr int OFF_K = OFF_U + CH * USZ * 2;
constexpr int OFF_R = OFF_K + CH * KCH * 2;
constexpr int SMEM = OFF_R + CH * SEQ * 4;
}

__global__ void __launch_bounds__(512, 1)
k2_conv(const bf16* __restrict__ x, const bf16* __restrict__ Dskip) {
  using namespace k2;
  extern __shared__ __align__(16) uint8_t sm[];
  const int tid = threadIdx.x, warp = tid >> 5, lane = tid & 31, g = lane >> 2, t = lane & 3;
  const int ch = warp >> 1, half = warp & 1;
  const int d0 = blockIdx.x * CH;
  bf16* us = reinterpret_cast<bf16*>(sm + OFF_U);
  bf16* ks = reinterpret_cast<bf16*>(sm + OFF_K);

  if (tid < CH * UPAD / 2) {
    const int c = tid / (UPAD / 2), o = tid % (UPAD / 2);
    reinterpret_cast<uint32_t*>(us + c * USZ)[o] = 0u;
  }
  {
    uint4 v[2][2];
#pragma unroll
    for (int it = 0; it < 2; it++) {
      const int l = 2 * (tid + it * 512);
      v[it][0] = __ldg(reinterpret_cast<const uint4*>(x + (size_t)l * DM + d0));
      v[it][1] = __ldg(reinterpret_cast<const uint4*>(x + (size_t)(l + 1) * DM + d0));
    }
    {
      const float* kq = g_kq + (d0 + ch) * 648;
      bf16* kr = ks + ch * KCH;
      bf16* kr2 = kr + KSZ + 16;
      for (int w = half * 528 + lane; w < (half + 1) * 528; w += 32) {
        float kv[3];
#pragma unroll
        for (int q = 0; q < 3; q++) {
          const int xk = KOFF - 2 * w - q;
          float val = 0.f;
          if (xk >= 0 && xk < SEQ) {
            const uint32_t pb = __float_as_uint(bfr((float)xk));
            const int id = xk < 256 ? xk : (256 + ((int)(pb >> 23) - 135) * 128 + (int)((pb >> 16) & 127));
            val = __ldg(kq + id);
          }
          kv[q] = val;
        }
        reinterpret_cast<uint32_t*>(kr)[w] = pack2(kv[0], kv[1]);
        reinterpret_cast<uint32_t*>(kr2)[w] = pack2(kv[1], kv[2]);
      }
    }
#pragma unroll
    for (int it = 0; it < 2; it++) {
      const int l = 2 * (tid + it * 512);
      const int e = l & 15;
      const int pe = ((e & 7) >> 1) * 4 + (e >> 3) * 2;
      const int pos = UPAD + (l & ~15) + pe;
      const uint32_t a[4] = {v[it][0].x, v[it][0].y, v[it][0].z, v[it][0].w};
      const uint32_t b[4] = {v[it][1].x, v[it][1].y, v[it][1].z, v[it][1].w};
#pragma unroll
      for (int c = 0; c < 4; c++) {
        *reinterpret_cast<uint32_t*>(us + (2 * c) * USZ + pos) = __byte_perm(a[c], b[c], 0x5410);
        *reinterpret_cast<uint32_t*>(us + (2 * c + 1) * USZ + pos) = __byte_perm(a[c], b[c], 0x7632);
      }
    }
  }
  __syncthreads();

  float D[16][4];
#pragma unroll
  for (int j = 0; j < 16; j++)
#pragma unroll
    for (int q = 0; q < 4; q++) D[j][q] = 0.f;
  const bf16* uc = us + ch * USZ + UPAD;
  {
    const bf16* kr = ks + ch * KCH;
    const uint32_t* fbase = reinterpret_cast<const uint32_t*>((g & 1) ? (kr + KSZ + 16) : kr) + ((KOFF - g + 2 * t) >> 1);
    for (int r = half * 4; r < half * 4 + 4; r++) {
      uint32_t B[16][2];
#pragma unroll
      for (int j = 0; j < 16; j++) {
        const uint2 v = *reinterpret_cast<const uint2*>(uc + 16 * (8 * j - r + g) + 4 * t);
        B[j][0] = v.x; B[j][1] = v.y;
      }
      uint32_t fm1 = fbase[-4 * (2 * r - 1)];
#pragma unroll
      for (int k = 0; k < 16; k++) {
        const int dl = 8 * k + r;
        const uint32_t f0 = fbase[-4 * (2 * dl)];
        const uint32_t f1 = fbase[-4 * (2 * dl + 1)];
        if (k > 0) fm1 = fbase[-4 * (2 * dl - 1)];
#pragma unroll
        for (int j = k; j < 16; j++) mma_bf16(D[j], f0, f1, fm1, f0, B[j - k][0], B[j - k][1]);
      }
    }
  }
  float* red = reinterpret_cast<float*>(sm + OFF_R) + ch * SEQ;
  if (half == 1) {
#pragma unroll
    for (int j = 0; j < 16; j++) *reinterpret_cast<float4*>(red + (j * 32 + lane) * 4) = make_float4(D[j][0], D[j][1], D[j][2], D[j][3]);
  }
  __syncthreads();
  if (half == 0) {
    const float dsk = __bfloat162float(Dskip[d0 + ch]);
    bf16* st = ks;
#pragma unroll
    for (int j = 0; j < 16; j++) {
      const float4 o = *reinterpret_cast<const float4*>(red + (j * 32 + lane) * 4);
      const float dd[4] = {D[j][0] + o.x, D[j][1] + o.y, D[j][2] + o.z, D[j][3] + o.w};
#pragma unroll
      for (int q = 0; q < 4; q++) {
        const int a = 8 * j + 2 * t + (q & 1), bb = g + (q >> 1) * 8;
        const int l = 16 * a + bb;
        const int pe = ((bb & 7) >> 1) * 4 + (bb >> 3) * 2 + (bb & 1);
        const float uv = __bfloat162float(uc[16 * a + pe]);
        const float y = bfr(dd[q]) + bfr(uv * dsk);
        st[l * 8 + ((ch + 2 * t) & 7)] = __float2bfloat16_rn(y);
      }
    }
  }
  __syncthreads();
  for (int l = tid; l < SEQ; l += 512) {
    const uint4 v = *reinterpret_cast<const uint4*>(ks + l * 8);
    const int rot = ((l >> 5) & 3);
    uint32_t w[4] = {v.x, v.y, v.z, v.w};
    uint32_t o[4];
#pragma unroll
    for (int i = 0; i < 4; i++) o[i] = rot == 0 ? w[i] : rot == 1 ? w[(i + 1) & 3] : rot == 2 ? w[(i + 2) & 3] : w[(i + 3) & 3];
    *reinterpret_cast<uint4*>(g_b + (size_t)l * DM + d0) = make_uint4(o[0], o[1], o[2], o[3]);
  }
}

typedef CUresult (*EncodeFn)(CUtensorMap*, CUtensorMapDataType, cuuint32_t, void*, const cuuint64_t*, const cuuint64_t*,
                             const cuuint32_t*, const cuuint32_t*, CUtensorMapInterleave, CUtensorMapSwizzle,
                             CUtensorMapL2promotion, CUtensorMapFloatOOBfill);

static void make_map(EncodeFn enc, CUtensorMap* m, void* ptr, uint64_t inner, uint64_t outer, uint32_t bi, uint32_t bo) {
  cuuint64_t dims[2] = {inner, outer};
  cuuint64_t strides[1] = {inner * 2};
  cuuint32_t box[2] = {bi, bo};
  cuuint32_t es[2] = {1, 1};
  enc(m, CU_TENSOR_MAP_DATA_TYPE_BFLOAT16, 2, ptr, dims, strides, box, es, CU_TENSOR_MAP_INTERLEAVE_NONE,
      CU_TENSOR_MAP_SWIZZLE_128B, CU_TENSOR_MAP_L2_PROMOTION_L2_256B, CU_TENSOR_MAP_FLOAT_OOB_FILL_NONE);
}

extern "C" void kernel_launch(void* const* d_in, const int* in_sizes, int n_in, void* d_out, int out_size) {
  const bf16* x = (const bf16*)d_in[0];
  const bf16* wqkv = (const bf16*)d_in[1];
  const bf16* wo = (const bf16*)d_in[2];
  const bf16* logAr = (const bf16*)d_in[4];
  const bf16* Aim = (const bf16*)d_in[5];
  const bf16* Cre = (const bf16*)d_in[6];
  const bf16* Cim = (const bf16*)d_in[7];
  const bf16* logdt = (const bf16*)d_in[8];
  const bf16* Dskip = (const bf16*)d_in[9];
  const bf16* gatew = (const bf16*)d_in[10];

  static EncodeFn enc = nullptr;
  static void* p_o = nullptr;
  if (!enc) {
    void* fn = nullptr;
    cudaDriverEntryPointQueryResult qr;
    cudaGetDriverEntryPoint("cuTensorMapEncodeTiled", &fn, cudaEnableDefault, &qr);
    enc = (EncodeFn)fn;
    cudaGetSymbolAddress(&p_o, g_o);
    cudaFuncSetAttribute(k1_qkv_attn, cudaFuncAttributeMaxDynamicSharedMemorySize, k1::SMEM);
    cudaFuncSetAttribute(k2_conv, cudaFuncAttributeMaxDynamicSharedMemorySize, k2::SMEM);
    cudaFuncSetAttribute(k3_out, cudaFuncAttributeMaxDynamicSharedMemorySize, k3::SMEM);
  }
  CUtensorMap tmx, tmw, tmo, tmwo;
  make_map(enc, &tmx, (void*)x, 1024, 2048, 64, 128);
  make_map(enc, &tmw, (void*)wqkv, 3072, 1024, 64, 64);
  make_map(enc, &tmo, p_o, 1024, 2048, 64, 64);
  make_map(enc, &tmwo, (void*)wo, 1024, 1024, 64, 64);

  k0_kgen<<<128, 256>>>(x, logAr, Aim, Cre, Cim, logdt, gatew);
  k2_conv<<<128, 512, k2::SMEM>>>(x, Dskip);
  k1_qkv_attn<<<128, 384, k1::SMEM>>>(tmx, tmw);
  k3_out<<<128, 384, k3::SMEM>>>(tmo, tmwo, (bf16*)d_out);
}
```

```cpp
#include <cuda_runtime.h>
#include <cuda_bf16.h>
#include <cuda.h>
#include <stdint.h>

typedef __nv_bfloat16 bf16;

constexpr int SEQ = 2048, DM = 1024, NMODE = 128;

__device__ __align__(1024) bf16 g_o[SEQ * DM];
__device__ __align__(1024) bf16 g_b[SEQ * DM];
__device__ float g_gate[SEQ];
__device__ __align__(16) float g_part[16 * 8 * 2 * 1056];
__device__ unsigned int g_cnt[16];

__device__ __forceinline__ uint32_t smem_u32(const void* p) { return (uint32_t)__cvta_generic_to_shared(p); }
__device__ __forceinline__ void mbar_init(uint32_t bar, uint32_t cnt) {
  asm volatile("mbarrier.init.shared::cta.b64 [%0], %1;" ::"r"(bar), "r"(cnt));
}
__device__ __forceinline__ void mbar_expect_tx(uint32_t bar, uint32_t bytes) {
  asm volatile("mbarrier.arrive.expect_tx.shared::cta.b64 _, [%0], %1;" ::"r"(bar), "r"(bytes) : "memory");
}
__device__ __forceinline__ void mbar_arrive_cluster(uint32_t bar, uint32_t cta) {
  asm volatile(
      "{\n.reg .b32 ra;\nmapa.shared::cluster.u32 ra, %0, %1;\n"
      "mbarrier.arrive.shared::cluster.b64 _, [ra];\n}\n" ::"r"(bar), "r"(cta) : "memory");
}
__device__ __forceinline__ bool mbar_try_wait(uint32_t bar, uint32_t parity) {
  uint32_t ok;
  asm volatile(
      "{\n.reg .pred p;\nmbarrier.try_wait.parity.shared::cta.b64 p, [%1], %2;\nselp.u32 %0, 1, 0, p;\n}\n"
      : "=r"(ok) : "r"(bar), "r"(parity) : "memory");
  return ok;
}
__device__ __forceinline__ void mbar_wait(uint32_t bar, uint32_t parity) {
  while (!mbar_try_wait(bar, parity)) {}
}
__device__ __forceinline__ void tma_load_2d(uint32_t dst, const CUtensorMap* map, uint32_t bar, int c0, int c1) {
  asm volatile(
      "cp.async.bulk.tensor.2d.shared::cluster.global.mbarrier::complete_tx::bytes [%0], [%1, {%3, %4}], [%2];" ::"r"(dst),
      "l"(map), "r"(bar), "r"(c0), "r"(c1) : "memory");
}
__device__ __forceinline__ void tma_load_2d_mc(uint32_t dst, const CUtensorMap* map, uint32_t bar, int c0, int c1,
                                               uint16_t mask) {
  asm volatile(
      "cp.async.bulk.tensor.2d.shared::cluster.global.mbarrier::complete_tx::bytes.multicast::cluster [%0], [%1, {%3, %4}], [%2], %5;" ::"r"(dst),
      "l"(map), "r"(bar), "r"(c0), "r"(c1), "h"(mask) : "memory");
}
__device__ __forceinline__ void cluster_sync_all() {
  asm volatile("barrier.cluster.arrive.release.aligned;\nbarrier.cluster.wait.acquire.aligned;\n" ::: "memory");
}
__device__ __forceinline__ uint32_t cluster_ctarank() {
  uint32_t r; asm volatile("mov.u32 %0, %%cluster_ctarank;" : "=r"(r)); return r;
}
__device__ __forceinline__ void named_bar_sync(int id, int n) { asm volatile("bar.sync %0, %1;" ::"r"(id), "r"(n) : "memory"); }
__device__ __forceinline__ void fence_async_smem() { asm volatile("fence.proxy.async.shared::cta;" ::: "memory"); }
__device__ __forceinline__ void wg_fence() { asm volatile("wgmma.fence.sync.aligned;" ::: "memory"); }
__device__ __forceinline__ void wg_commit() { asm volatile("wgmma.commit_group.sync.aligned;" ::: "memory"); }
template <int N> __device__ __forceinline__ void wg_wait() { asm volatile("wgmma.wait_group.sync.aligned %0;" ::"n"(N) : "memory"); }
__device__ __forceinline__ uint64_t make_desc(uint32_t addr, uint32_t lbo, uint32_t sbo) {
  return (uint64_t)((addr & 0x3FFFF) >> 4) | ((uint64_t)(lbo >> 4) << 16) | ((uint64_t)(sbo >> 4) << 32) | (1ull << 62);
}
__device__ __forceinline__ float bfr(float x) { return __bfloat162float(__float2bfloat16_rn(x)); }
__device__ __forceinline__ uint32_t pack2(float lo, float hi) {
  __nv_bfloat162 v = __floats2bfloat162_rn(lo, hi);
  return *reinterpret_cast<uint32_t*>(&v);
}
__device__ __forceinline__ float ex2f(float x) { float r; asm("ex2.approx.ftz.f32 %0, %1;" : "=f"(r) : "f"(x)); return r; }
__device__ __forceinline__ float lo_f(uint32_t v) { return __uint_as_float(v << 16); }
__device__ __forceinline__ float hi_f(uint32_t v) { return __uint_as_float(v & 0xffff0000u); }
__device__ __forceinline__ uint32_t phi2(float a0, float a1) {
  const uint32_t t2 = pack2(a0, a1);
  const float t0 = lo_f(t2), t1 = hi_f(t2);
  const float e0 = ex2f(t0 * 1.4426950408889634f), e1 = ex2f(t1 * 1.4426950408889634f);
  const float f0 = t0 > 0.f ? t0 + 1.0f : e0;
  const float f1 = t1 > 0.f ? t1 + 1.0f : e1;
  const uint32_t f2 = pack2(f0, f1);
  return pack2(lo_f(f2) + 1e-6f, hi_f(f2) + 1e-6f);
}
template <int R> __device__ __forceinline__ void fence_regs(float (&d)[R]) {
#pragma unroll
  for (int i = 0; i < R; i++) asm volatile("" : "+f"(d[i])::"memory");
}

__device__ __forceinline__ void wgmma_ss_n192_tb(float (&d)[96], uint64_t da, uint64_t db, int sc) {
  asm volatile("{\n.reg .pred p;\nsetp.ne.b32 p, %98, 0;\n"
    "wgmma.mma_async.sync.aligned.m64n192k16.f32.bf16.bf16 {%0, %1, %2, %3, %4, %5, %6, %7, %8, %9, %10, %11, %12, %13, %14, %15, %16, %17, %18, %19, %20, %21, %22, %23, %24, %25, %26, %27, %28, %29, %30, %31, %32, %33, %34, %35, %36, %37, %38, %39, %40, %41, %42, %43, %44, %45, %46, %47, %48, %49, %50, %51, %52, %53, %54, %55, %56, %57, %58, %59, %60, %61, %62, %63, %64, %65, %66, %67, %68, %69, %70, %71, %72, %73, %74, %75, %76, %77, %78, %79, %80, %81, %82, %83, %84, %85, %86, %87, %88, %89, %90, %91, %92, %93, %94, %95}, %96, %97, p, 1, 1, 0, 1;\n}\n"
    : "+f"(d[0]), "+f"(d[1]), "+f"(d[2]), "+f"(d[3]), "+f"(d[4]), "+f"(d[5]), "+f"(d[6]), "+f"(d[7]), "+f"(d[8]), "+f"(d[9]), "+f"(d[10]), "+f"(d[11]), "+f"(d[12]), "+f"(d[13]), "+f"(d[14]), "+f"(d[15]), "+f"(d[16]), "+f"(d[17]), "+f"(d[18]), "+f"(d[19]), "+f"(d[20]), "+f"(d[21]), "+f"(d[22]), "+f"(d[23]), "+f"(d[24]), "+f"(d[25]), "+f"(d[26]), "+f"(d[27]), "+f"(d[28]), "+f"(d[29]), "+f"(d[30]), "+f"(d[31]), "+f"(d[32]), "+f"(d[33]), "+f"(d[34]), "+f"(d[35]), "+f"(d[36]), "+f"(d[37]), "+f"(d[38]), "+f"(d[39]), "+f"(d[40]), "+f"(d[41]), "+f"(d[42]), "+f"(d[43]), "+f"(d[44]), "+f"(d[45]), "+f"(d[46]), "+f"(d[47]), "+f"(d[48]), "+f"(d[49]), "+f"(d[50]), "+f"(d[51]), "+f"(d[52]), "+f"(d[53]), "+f"(d[54]), "+f"(d[55]), "+f"(d[56]), "+f"(d[57]), "+f"(d[58]), "+f"(d[59]), "+f"(d[60]), "+f"(d[61]), "+f"(d[62]), "+f"(d[63]), "+f"(d[64]), "+f"(d[65]), "+f"(d[66]), "+f"(d[67]), "+f"(d[68]), "+f"(d[69]), "+f"(d[70]), "+f"(d[71]), "+f"(d[72]), "+f"(d[73]), "+f"(d[74]), "+f"(d[75]), "+f"(d[76]), "+f"(d[77]), "+f"(d[78]), "+f"(d[79]), "+f"(d[80]), "+f"(d[81]), "+f"(d[82]), "+f"(d[83]), "+f"(d[84]), "+f"(d[85]), "+f"(d[86]), "+f"(d[87]), "+f"(d[88]), "+f"(d[89]), "+f"(d[90]), "+f"(d[91]), "+f"(d[92]), "+f"(d[93]), "+f"(d[94]), "+f"(d[95])
    : "l"(da), "l"(db), "r"(sc));
}

__device__ __forceinline__ void wgmma_ss_n128_tb(float (&d)[64], uint64_t da, uint64_t db, int sc) {
  asm volatile("{\n.reg .pred p;\nsetp.ne.b32 p, %66, 0;\n"
    "wgmma.mma_async.sync.aligned.m64n128k16.f32.bf16.bf16 {%0, %1, %2, %3, %4, %5, %6, %7, %8, %9, %10, %11, %12, %13, %14, %15, %16, %17, %18, %19, %20, %21, %22, %23, %24, %25, %26, %27, %28, %29, %30, %31, %32, %33, %34, %35, %36, %37, %38, %39, %40, %41, %42, %43, %44, %45, %46, %47, %48, %49, %50, %51, %52, %53, %54, %55, %56, %57, %58, %59, %60, %61, %62, %63}, %64, %65, p, 1, 1, 0, 1;\n}\n"
    : "+f"(d[0]), "+f"(d[1]), "+f"(d[2]), "+f"(d[3]), "+f"(d[4]), "+f"(d[5]), "+f"(d[6]), "+f"(d[7]), "+f"(d[8]), "+f"(d[9]), "+f"(d[10]), "+f"(d[11]), "+f"(d[12]), "+f"(d[13]), "+f"(d[14]), "+f"(d[15]), "+f"(d[16]), "+f"(d[17]), "+f"(d[18]), "+f"(d[19]), "+f"(d[20]), "+f"(d[21]), "+f"(d[22]), "+f"(d[23]), "+f"(d[24]), "+f"(d[25]), "+f"(d[26]), "+f"(d[27]), "+f"(d[28]), "+f"(d[29]), "+f"(d[30]), "+f"(d[31]), "+f"(d[32]), "+f"(d[33]), "+f"(d[34]), "+f"(d[35]), "+f"(d[36]), "+f"(d[37]), "+f"(d[38]), "+f"(d[39]), "+f"(d[40]), "+f"(d[41]), "+f"(d[42]), "+f"(d[43]), "+f"(d[44]), "+f"(d[45]), "+f"(d[46]), "+f"(d[47]), "+f"(d[48]), "+f"(d[49]), "+f"(d[50]), "+f"(d[51]), "+f"(d[52]), "+f"(d[53]), "+f"(d[54]), "+f"(d[55]), "+f"(d[56]), "+f"(d[57]), "+f"(d[58]), "+f"(d[59]), "+f"(d[60]), "+f"(d[61]), "+f"(d[62]), "+f"(d[63])
    : "l"(da), "l"(db), "r"(sc));
}

__device__ __forceinline__ void wgmma_ss_n64_tatb(float (&d)[32], uint64_t da, uint64_t db, int sc) {
  asm volatile("{\n.reg .pred p;\nsetp.ne.b32 p, %34, 0;\n"
    "wgmma.mma_async.sync.aligned.m64n64k16.f32.bf16.bf16 {%0, %1, %2, %3, %4, %5, %6, %7, %8, %9, %10, %11, %12, %13, %14, %15, %16, %17, %18, %19, %20, %21, %22, %23, %24, %25, %26, %27, %28, %29, %30, %31}, %32, %33, p, 1, 1, 1, 1;\n}\n"
    : "+f"(d[0]), "+f"(d[1]), "+f"(d[2]), "+f"(d[3]), "+f"(d[4]), "+f"(d[5]), "+f"(d[6]), "+f"(d[7]), "+f"(d[8]), "+f"(d[9]), "+f"(d[10]), "+f"(d[11]), "+f"(d[12]), "+f"(d[13]), "+f"(d[14]), "+f"(d[15]), "+f"(d[16]), "+f"(d[17]), "+f"(d[18]), "+f"(d[19]), "+f"(d[20]), "+f"(d[21]), "+f"(d[22]), "+f"(d[23]), "+f"(d[24]), "+f"(d[25]), "+f"(d[26]), "+f"(d[27]), "+f"(d[28]), "+f"(d[29]), "+f"(d[30]), "+f"(d[31])
    : "l"(da), "l"(db), "r"(sc));
}

__device__ __forceinline__ void wgmma_ss_n8_tatb(float (&d)[4], uint64_t da, uint64_t db, int sc) {
  asm volatile("{\n.reg .pred p;\nsetp.ne.b32 p, %6, 0;\n"
    "wgmma.mma_async.sync.aligned.m64n8k16.f32.bf16.bf16 {%0, %1, %2, %3}, %4, %5, p, 1, 1, 1, 1;\n}\n"
    : "+f"(d[0]), "+f"(d[1]), "+f"(d[2]), "+f"(d[3])
    : "l"(da), "l"(db), "r"(sc));
}

__device__ __forceinline__ void wgmma_rs_n40_tb(float (&d)[20], uint32_t a0, uint32_t a1, uint32_t a2, uint32_t a3, uint64_t db, int sc) {
  asm volatile("{\n.reg .pred p;\nsetp.ne.b32 p, %25, 0;\n"
    "wgmma.mma_async.sync.aligned.m64n40k16.f32.bf16.bf16 {%0, %1, %2, %3, %4, %5, %6, %7, %8, %9, %10, %11, %12, %13, %14, %15, %16, %17, %18, %19}, {%20, %21, %22, %23}, %24, p, 1, 1, 1;\n}\n"
    : "+f"(d[0]), "+f"(d[1]), "+f"(d[2]), "+f"(d[3]), "+f"(d[4]), "+f"(d[5]), "+f"(d[6]), "+f"(d[7]), "+f"(d[8]), "+f"(d[9]), "+f"(d[10]), "+f"(d[11]), "+f"(d[12]), "+f"(d[13]), "+f"(d[14]), "+f"(d[15]), "+f"(d[16]), "+f"(d[17]), "+f"(d[18]), "+f"(d[19])
    : "r"(a0), "r"(a1), "r"(a2), "r"(a3), "l"(db), "r"(sc));
}


namespace k1 {
constexpr int BM = 256, BN = 192, BK = 64, ST = 4;
constexpr int A_BYTES = BM * BK * 2, B_BYTES = BK * BN * 2, STAGE = A_BYTES + B_BYTES;
constexpr int SMEM = ST * STAGE + 1024 + 256;
constexpr int OFF_PK = 0, OFF_V = 32768, OFF_ONES = 65536, OFF_KV = 69632, OFF_O = 81920, OFF_RED = 114688;
}

__global__ void __cluster_dims__(2, 1, 1) __launch_bounds__(384, 1)
k1_qkv_attn(const __grid_constant__ CUtensorMap tmx, const __grid_constant__ CUtensorMap tmw) {
  using namespace k1;
  extern __shared__ uint8_t smem_raw[];
  const uint32_t sbase = (smem_u32(smem_raw) + 1023) & ~1023u;
  uint8_t* sgen = smem_raw + (sbase - smem_u32(smem_raw));
  const uint32_t bars = sbase + ST * STAGE;
  const int tid = threadIdx.x, warp = tid >> 5, lane = tid & 31;
  const uint32_t rank = cluster_ctarank();
  const int cl = blockIdx.x >> 1;
  const int mt = cl >> 3;
  const int hp = ((cl & 7) << 1) + rank;
  const int m0 = mt * BM;

  if (tid == 0) {
    for (int s = 0; s < ST; s++) {
      mbar_init(bars + 8 * s, 1);
      mbar_init(bars + 8 * (ST + s), 16);
    }
    asm volatile("fence.mbarrier_init.release.cluster;" ::: "memory");
  }
  cluster_sync_all();

  if (warp >= 8) {
    asm volatile("setmaxnreg.dec.sync.aligned.u32 40;");
    if (warp == 8 && lane == 0) {
      for (int kb = 0; kb < DM / BK; kb++) {
        const int s = kb % ST;
        mbar_wait(bars + 8 * (ST + s), ((kb / ST) & 1) ^ 1);
        const uint32_t full = bars + 8 * s;
        mbar_expect_tx(full, STAGE);
        const uint32_t sa = sbase + s * STAGE, sb = sa + A_BYTES;
        tma_load_2d_mc(sa + rank * 16384, &tmx, full, kb * BK, m0 + rank * 128, (uint16_t)3);
#pragma unroll
        for (int j = 0; j < 3; j++) tma_load_2d(sb + j * 8192, &tmw, full, j * 1024 + hp * 64, kb * BK);
      }
    }
    cluster_sync_all();
  } else {
    asm volatile("setmaxnreg.inc.sync.aligned.u32 232;");
    const int wg = warp >> 2, w4 = warp & 3, g = lane >> 2, t = lane & 3;
    float acc[2][96];
#pragma unroll
    for (int i = 0; i < 96; i++) { acc[0][i] = 0.f; acc[1][i] = 0.f; }
    for (int kb = 0; kb < DM / BK; kb++) {
      const int s = kb % ST;
      mbar_wait(bars + 8 * s, (kb / ST) & 1);
      const uint32_t sa = sbase + s * STAGE + wg * 16384, sb = sbase + s * STAGE + A_BYTES;
      wg_fence();
#pragma unroll
      for (int ks = 0; ks < 4; ks++) {
        const uint64_t db = make_desc(sb + ks * 2048, 8192, 1024);
#pragma unroll
        for (int mb = 0; mb < 2; mb++) {
          const uint64_t da = make_desc(sa + mb * 8192 + ks * 32, 16, 1024);
          wgmma_ss_n192_tb(acc[mb], da, db, 1);
        }
      }
      wg_commit();
      if (kb > 0) {
        wg_wait<1>();
        const int sp = (kb - 1) % ST;
        if (lane == 0) { mbar_arrive_cluster(bars + 8 * (ST + sp), 0); mbar_arrive_cluster(bars + 8 * (ST + sp), 1); }
      }
    }
    wg_wait<0>();
    fence_regs(acc[0]); fence_regs(acc[1]);
    named_bar_sync(1, 256);

#pragma unroll
    for (int mb = 0; mb < 2; mb++) {
#pragma unroll
      for (int h = 0; h < 2; h++) {
        const int r = wg * 128 + mb * 64 + w4 * 16 + g + h * 8;
#pragma unroll
        for (int j = 0; j < 8; j++) {
          const uint32_t off = r * 128 + ((j ^ (r & 7)) << 4) + t * 4;
          const float k0 = acc[mb][4 * (8 + j) + 2 * h], k1v = acc[mb][4 * (8 + j) + 2 * h + 1];
          const float v0 = acc[mb][4 * (16 + j) + 2 * h], v1 = acc[mb][4 * (16 + j) + 2 * h + 1];
          *reinterpret_cast<uint32_t*>(sgen + OFF_PK + off) = phi2(k0, k1v);
          *reinterpret_cast<uint32_t*>(sgen + OFF_V + off) = pack2(v0, v1);
        }
      }
    }
    if (tid < 256) *reinterpret_cast<uint32_t*>(sgen + OFF_ONES + tid * 4) = 0x3F803F80u;
    fence_async_smem();
    named_bar_sync(1, 256);

    float* part = g_part + (size_t)(hp * 8 + mt) * 2112;
    {
      float kv[32], zz[4];
#pragma unroll
      for (int i = 0; i < 32; i++) kv[i] = 0.f;
#pragma unroll
      for (int i = 0; i < 4; i++) zz[i] = 0.f;
      wg_fence();
#pragma unroll
      for (int ks = 0; ks < 8; ks++) {
        const uint64_t da = make_desc(sbase + OFF_PK + wg * 16384 + ks * 2048, 16, 1024);
        const uint64_t db = make_desc(sbase + OFF_V + wg * 16384 + ks * 2048, 16, 1024);
        const uint64_t d1 = make_desc(sbase + OFF_ONES, 16, 0);
        wgmma_ss_n64_tatb(kv, da, db, 1);
        wgmma_ss_n8_tatb(zz, da, d1, 1);
      }
      wg_commit();
      wg_wait<0>();
      fence_regs(kv); fence_regs(zz);
      const int hh = w4 >> 1;
      float* red = reinterpret_cast<float*>(sgen + OFF_RED);
      float vals[2][4][2];
#pragma unroll
      for (int h = 0; h < 2; h++)
#pragma unroll
        for (int j = 0; j < 4; j++) {
          vals[h][j][0] = hh ? kv[4 * (4 + j) + 2 * h] : kv[4 * j + 2 * h];
          vals[h][j][1] = hh ? kv[4 * (4 + j) + 2 * h + 1] : kv[4 * j + 2 * h + 1];
        }
      if (wg == 1) {
#pragma unroll
        for (int h = 0; h < 2; h++) {
          const int d = (w4 & 1) * 16 + g + h * 8;
#pragma unroll
          for (int j = 0; j < 4; j++)
            *reinterpret_cast<float2*>(red + hh * 1056 + d * 32 + 8 * j + 2 * t) = make_float2(vals[h][j][0], vals[h][j][1]);
          if (t == 0) red[hh * 1056 + 1024 + d] = zz[2 * h];
        }
      }
      named_bar_sync(1, 256);
      if (wg == 0) {
#pragma unroll
        for (int h = 0; h < 2; h++) {
          const int d = (w4 & 1) * 16 + g + h * 8;
#pragma unroll
          for (int j = 0; j < 4; j++) {
            const float2 o = *reinterpret_cast<const float2*>(red + hh * 1056 + d * 32 + 8 * j + 2 * t);
            *reinterpret_cast<float2*>(part + hh * 1056 + d * 32 + 8 * j + 2 * t) = make_float2(vals[h][j][0] + o.x, vals[h][j][1] + o.y);
          }
          if (t == 0) part[hh * 1056 + 1024 + d] = zz[2 * h] + red[hh * 1056 + 1024 + d];
        }
        __threadfence();
        named_bar_sync(2, 128);
        if (tid == 0) atomicAdd(&g_cnt[hp], 1u);
      }
    }
    uint32_t pq[2][4][4];
#pragma unroll
    for (int mb = 0; mb < 2; mb++)
#pragma unroll
      for (int kk = 0; kk < 4; kk++) {
        pq[mb][kk][0] = phi2(acc[mb][8 * kk + 0], acc[mb][8 * kk + 1]);
        pq[mb][kk][1] = phi2(acc[mb][8 * kk + 2], acc[mb][8 * kk + 3]);
        pq[mb][kk][2] = phi2(acc[mb][8 * kk + 4], acc[mb][8 * kk + 5]);
        pq[mb][kk][3] = phi2(acc[mb][8 * kk + 6], acc[mb][8 * kk + 7]);
      }
    if (tid == 0) {
      unsigned int v;
      do { asm volatile("ld.acquire.gpu.global.u32 %0, [%1];" : "=r"(v) : "l"(&g_cnt[hp]) : "memory"); } while (v < 8u);
    }
    named_bar_sync(1, 256);
    {
      const float* pb = g_part + (size_t)(hp * 8) * 2112;
      for (int i = tid; i < 528; i += 256) {
        float4 s4 = make_float4(0.f, 0.f, 0.f, 0.f);
#pragma unroll
        for (int p = 0; p < 8; p++) {
          float4 v4 = __ldcg(reinterpret_cast<const float4*>(pb + p * 2112) + i);
          s4.x += v4.x; s4.y += v4.y; s4.z += v4.z; s4.w += v4.w;
        }
        const int hh = i / 264, rem = i - hh * 264;
        uint8_t* tile = sgen + OFF_KV + hh * 4096;
        if (rem < 256) {
          const int d = rem >> 3, e = (rem & 7) * 4;
          const uint32_t off = d * 128 + (((e >> 3) ^ (d & 7)) << 4) + (e & 7) * 2;
          *reinterpret_cast<uint2*>(tile + off) = make_uint2(pack2(s4.x, s4.y), pack2(s4.z, s4.w));
        } else {
          const int d0 = (rem - 256) * 4;
          float zv[4] = {s4.x, s4.y, s4.z, s4.w};
#pragma unroll
          for (int q = 0; q < 4; q++) {
            const int d = d0 + q;
            const uint32_t off = d * 128 + ((4 ^ (d & 7)) << 4);
            *reinterpret_cast<uint4*>(tile + off) = make_uint4(pack2(zv[q], 0.f), 0u, 0u, 0u);
          }
        }
      }
    }
    fence_async_smem();
    named_bar_sync(1, 256);
#pragma unroll
    for (int mb = 0; mb < 2; mb++) {
#pragma unroll
      for (int hh = 0; hh < 2; hh++) {
        float num[20];
#pragma unroll
        for (int i = 0; i < 20; i++) num[i] = 0.f;
        wg_fence();
#pragma unroll
        for (int kk = 0; kk < 2; kk++) {
          const uint64_t db = make_desc(sbase + OFF_KV + hh * 4096 + kk * 2048, 16, 1024);
          wgmma_rs_n40_tb(num, pq[mb][hh * 2 + kk][0], pq[mb][hh * 2 + kk][1], pq[mb][hh * 2 + kk][2], pq[mb][hh * 2 + kk][3], db, 1);
        }
        wg_commit();
        wg_wait<0>();
        fence_regs(num);
#pragma unroll
        for (int h = 0; h < 2; h++) {
          float den = __shfl_sync(0xffffffffu, num[16 + 2 * h], lane & ~3);
          den = bfr(bfr(den) + 1e-6f);
          const float rden = 1.0f / den;
          const int r = wg * 128 + mb * 64 + w4 * 16 + g + h * 8;
#pragma unroll
          for (int j = 0; j < 4; j++) {
            const uint32_t n2 = pack2(num[4 * j + 2 * h], num[4 * j + 2 * h + 1]);
            const float o0 = lo_f(n2) * rden, o1 = hi_f(n2) * rden;
            const uint32_t off = r * 128 + (((hh * 4 + j) ^ (r & 7)) << 4) + t * 4;
            *reinterpret_cast<uint32_t*>(sgen + OFF_O + off) = pack2(o0, o1);
          }
        }
      }
    }
    named_bar_sync(1, 256);
    for (int i = tid; i < 256 * 8; i += 256) {
      const int r = i >> 3, c = i & 7;
      uint4 v = *reinterpret_cast<const uint4*>(sgen + OFF_O + r * 128 + ((c ^ (r & 7)) << 4));
      *reinterpret_cast<uint4*>(g_o + (size_t)(m0 + r) * DM + hp * 64 + c * 8) = v;
    }
    cluster_sync_all();
  }
}

namespace k3 {
constexpr int BM = 128, BN = 128, BK = 64, ST = 5;
constexpr int A_BYTES = BM * BK * 2, B_BYTES = BK * BN * 2, STAGE = A_BYTES + B_BYTES;
constexpr int OFF_BT = ST * STAGE;
constexpr int OFF_BAR = OFF_BT + 32768;
constexpr int SMEM = OFF_BAR + 1024 + 256;
}

__global__ void __cluster_dims__(2, 1, 1) __launch_bounds__(384, 1)
k3_out(const __grid_constant__ CUtensorMap tmo, const __grid_constant__ CUtensorMap tmw,
       const __grid_constant__ CUtensorMap tmbt, const __grid_constant__ CUtensorMap tmout) {
  using namespace k3;
  extern __shared__ uint8_t smem_raw[];
  const uint32_t sbase = (smem_u32(smem_raw) + 1023) & ~1023u;
  uint8_t* sgen = smem_raw + (sbase - smem_u32(smem_raw));
  const uint32_t bars = sbase + OFF_BAR;
  const uint32_t barbt = bars + 8 * 2 * ST;
  const int tid = threadIdx.x, warp = tid >> 5, lane = tid & 31;
  const uint32_t rank = cluster_ctarank();
  const int cl = blockIdx.x >> 1;
  const int mt = cl >> 2;
  const int nt = ((cl & 3) << 1) + rank;
  const int m0 = mt * BM, n0 = nt * BN;
  if (blockIdx.x == 0 && tid < 16) g_cnt[tid] = 0;

  if (tid == 0) {
    for (int s = 0; s < ST; s++) {
      mbar_init(bars + 8 * s, 1);
      mbar_init(bars + 8 * (ST + s), 16);
    }
    mbar_init(barbt, 1);
    asm volatile("fence.mbarrier_init.release.cluster;" ::: "memory");
  }
  cluster_sync_all();

  if (warp >= 8) {
    asm volatile("setmaxnreg.dec.sync.aligned.u32 40;");
    if (warp == 8 && lane == 0) {
      for (int kb = 0; kb < DM / BK; kb++) {
        const int s = kb % ST;
        mbar_wait(bars + 8 * (ST + s), ((kb / ST) & 1) ^ 1);
        const uint32_t full = bars + 8 * s;
        mbar_expect_tx(full, STAGE);
        const uint32_t sa = sbase + s * STAGE, sb = sa + A_BYTES;
        tma_load_2d_mc(sa + rank * 8192, &tmo, full, kb * BK, m0 + rank * 64, (uint16_t)3);
#pragma unroll
        for (int j = 0; j < 2; j++) tma_load_2d(sb + j * 8192, &tmw, full, n0 + j * 64, kb * BK);
        if (kb == 2) {
          mbar_expect_tx(barbt, 32768);
          tma_load_2d(sbase + OFF_BT, &tmbt, barbt, m0, n0);
          tma_load_2d(sbase + OFF_BT + 16384, &tmbt, barbt, m0 + 64, n0);
        }
      }
    }
    cluster_sync_all();
  } else {
    asm volatile("setmaxnreg.inc.sync.aligned.u32 232;");
    const int wg = warp >> 2, w4 = warp & 3, g = lane >> 2, t = lane & 3;
    float acc[64];
#pragma unroll
    for (int i = 0; i < 64; i++) acc[i] = 0.f;
    for (int kb = 0; kb < DM / BK; kb++) {
      const int s = kb % ST;
      mbar_wait(bars + 8 * s, (kb / ST) & 1);
      const uint32_t sa = sbase + s * STAGE + wg * 8192, sb = sbase + s * STAGE + A_BYTES;
      wg_fence();
#pragma unroll
      for (int ks = 0; ks < 4; ks++) {
        const uint64_t db = make_desc(sb + ks * 2048, 8192, 1024);
        const uint64_t da = make_desc(sa + ks * 32, 16, 1024);
        wgmma_ss_n128_tb(acc, da, db, 1);
      }
      wg_commit();
      if (kb > 0) {
        wg_wait<1>();
        const int sp = (kb - 1) % ST;
        if (lane == 0) { mbar_arrive_cluster(bars + 8 * (ST + sp), 0); mbar_arrive_cluster(bars + 8 * (ST + sp), 1); }
      }
    }
    wg_wait<0>();
    fence_regs(acc);
    named_bar_sync(1, 256);
    mbar_wait(barbt, 0);
#pragma unroll
    for (int h = 0; h < 2; h++) {
      const int rl = wg * 64 + w4 * 16 + g + h * 8;
      const float gt = g_gate[m0 + rl];
      const float omg = bfr(1.0f - gt);
      const uint8_t* bt = sgen + OFF_BT + wg * 16384;
      const int ll = rl & 63;
#pragma unroll
      for (int j = 0; j < 16; j++) {
        const int c = 8 * j + 2 * t;
        const float b0 = __bfloat162float(*reinterpret_cast<const bf16*>(bt + c * 128 + (((ll >> 3) ^ (c & 7)) << 4) + (ll & 7) * 2));
        const float b1 = __bfloat162float(*reinterpret_cast<const bf16*>(bt + (c + 1) * 128 + (((ll >> 3) ^ ((c + 1) & 7)) << 4) + (ll & 7) * 2));
        const uint32_t a2 = pack2(acc[4 * j + 2 * h], acc[4 * j + 2 * h + 1]);
        const float o0 = bfr(gt * lo_f(a2)) + bfr(omg * b0);
        const float o1 = bfr(gt * hi_f(a2)) + bfr(omg * b1);
        *reinterpret_cast<uint32_t*>(sgen + (j >> 3) * 16384 + rl * 128 + (((j & 7) ^ (rl & 7)) << 4) + t * 4) = pack2(o0, o1);
      }
    }
    fence_async_smem();
    named_bar_sync(2 + wg, 128);
    if ((tid & 127) == 0) {
#pragma unroll
      for (int j = 0; j < 2; j++)
        asm volatile("cp.async.bulk.tensor.2d.global.shared::cta.bulk_group [%0, {%2, %3}], [%1];" ::"l"(&tmout),
                     "r"(sbase + j * 16384 + wg * 8192), "r"(n0 + j * 64), "r"(m0 + wg * 64) : "memory");
      asm volatile("cp.async.bulk.commit_group;" ::: "memory");
      asm volatile("cp.async.bulk.wait_group.read 0;" ::: "memory");
    }
    cluster_sync_all();
  }
}

__device__ float g_kq[DM * 648];
constexpr int KOFF = 2048 + 16;
constexpr int KSZ = 2112;
constexpr int KCH = 2 * KSZ + 16;
__device__ __align__(16) bf16 g_kr[DM * KCH];
__device__ __align__(1024) bf16 g_bT[DM * SEQ];

__device__ __forceinline__ void mma_bf16(float (&d)[4], uint32_t a0, uint32_t a1, uint32_t a2, uint32_t a3, uint32_t b0, uint32_t b1) {
  asm volatile("mma.sync.aligned.m16n8k16.row.col.f32.bf16.bf16.f32 {%0,%1,%2,%3}, {%4,%5,%6,%7}, {%8,%9}, {%0,%1,%2,%3};"
               : "+f"(d[0]), "+f"(d[1]), "+f"(d[2]), "+f"(d[3]) : "r"(a0), "r"(a1), "r"(a2), "r"(a3), "r"(b0), "r"(b1));
}
__device__ __forceinline__ void mma_tf32(float (&d)[4], uint32_t a0, uint32_t a1, uint32_t a2, uint32_t a3, uint32_t b0, uint32_t b1) {
  asm volatile("mma.sync.aligned.m16n8k8.row.col.f32.tf32.tf32.f32 {%0,%1,%2,%3}, {%4,%5,%6,%7}, {%8,%9}, {%0,%1,%2,%3};"
               : "+f"(d[0]), "+f"(d[1]), "+f"(d[2]), "+f"(d[3]) : "r"(a0), "r"(a1), "r"(a2), "r"(a3), "r"(b0), "r"(b1));
}
__device__ __forceinline__ uint32_t tf32r(float x) { uint32_t r; asm("cvt.rna.tf32.f32 %0, %1;" : "=r"(r) : "f"(x)); return r; }
struct cf { float r, i; };
__device__ __forceinline__ cf cmul(cf a, cf b) { cf c; c.r = a.r * b.r - a.i * b.i; c.i = a.r * b.i + a.i * b.r; return c; }
__device__ __forceinline__ cf csq(cf a) { cf c; c.r = a.r * a.r - a.i * a.i; c.i = 2.f * a.r * a.i; return c; }
__device__ __forceinline__ cf cexpp(float ar, float ai, float p) {
  const float e = ex2f(ar * p * 1.4426950408889634f);
  const float th = ai * p;
  const float k = rintf(th * 0.15915494309189535f);
  float r = fmaf(k, -6.2831854820251465f, th);
  r = fmaf(k, 1.7484556000744e-7f, r);
  cf w; w.r = e * __cosf(r); w.i = e * __sinf(r); return w;
}

__device__ __forceinline__ void kgen_channel(int d, int lane, const bf16* __restrict__ logAr, const bf16* __restrict__ Aim,
                                             const bf16* __restrict__ Cre, const bf16* __restrict__ Cim,
                                             const bf16* __restrict__ logdt) {
  const int g = lane >> 2, t = lane & 3;
  const float dt = bfr(ex2f(__bfloat162float(logdt[d]) * 1.4426950408889634f));
  float acc[5][4];
#pragma unroll
  for (int a = 0; a < 5; a++)
#pragma unroll
    for (int b = 0; b < 4; b++) acc[a][b] = 0.f;
  float last = 0.f;
#pragma unroll 2
  for (int n0 = 0; n0 < NMODE; n0 += 4) {
    const int idx = d * NMODE + n0 + t;
    const float ar = -bfr(ex2f(__bfloat162float(logAr[idx]) * 1.4426950408889634f)) * dt;
    const float ai = __bfloat162float(Aim[idx]) * dt;
    cf C; C.r = __bfloat162float(Cre[idx]) * dt; C.i = __bfloat162float(Cim[idx]) * dt;
    const cf Y1 = cexpp(ar, ai, (float)g);
    const cf Y8 = cexpp(ar, ai, (float)(8 * g));
    const cf W64 = cexpp(ar, ai, 64.f);
    const cf Y2 = csq(Y1), Y4 = csq(Y2);
    const cf Y16 = csq(Y8), Y32 = csq(Y16), Y64 = csq(Y32);
    const cf W128 = csq(W64), W256 = csq(W128), W512 = csq(W256), W1024 = csq(W512);
    const cf X0a = cmul(C, Y8), X0b = cmul(X0a, W64);
    const cf X1a = cmul(X0a, W128), X1b = cmul(X0b, W128);
    const cf X2a = cmul(cmul(C, W256), Y16), X2b = cmul(X2a, W128);
    const cf X3a = cmul(cmul(C, W512), Y32), X3b = cmul(X3a, W256);
    const cf C4 = cmul(C, W1024);
    const cf X4a = cmul(C4, Y64), X4b = cmul(X4a, W512);
    last += C4.r * W1024.r - C4.i * W1024.i;
    const uint32_t y1r = tf32r(Y1.r), y1i = tf32r(Y1.i);
    mma_tf32(acc[0], tf32r(X0a.r), tf32r(X0b.r), tf32r(-X0a.i), tf32r(-X0b.i), y1r, y1i);
    mma_tf32(acc[1], tf32r(X1a.r), tf32r(X1b.r), tf32r(-X1a.i), tf32r(-X1b.i), y1r, y1i);
    mma_tf32(acc[2], tf32r(X2a.r), tf32r(X2b.r), tf32r(-X2a.i), tf32r(-X2b.i), tf32r(Y2.r), tf32r(Y2.i));
    mma_tf32(acc[3], tf32r(X3a.r), tf32r(X3b.r), tf32r(-X3a.i), tf32r(-X3b.i), tf32r(Y4.r), tf32r(Y4.i));
    mma_tf32(acc[4], tf32r(X4a.r), tf32r(X4b.r), tf32r(-X4a.i), tf32r(-X4b.i), tf32r(Y8.r), tf32r(Y8.i));
  }
  float* kq = g_kq + d * 648;
#pragma unroll
  for (int a = 0; a < 5; a++) {
    *reinterpret_cast<float2*>(kq + 128 * a + 8 * g + 2 * t) = make_float2(2.f * acc[a][0], 2.f * acc[a][1]);
    *reinterpret_cast<float2*>(kq + 128 * a + 8 * (g + 8) + 2 * t) = make_float2(2.f * acc[a][2], 2.f * acc[a][3]);
  }
  last += __shfl_xor_sync(0xffffffffu, last, 1);
  last += __shfl_xor_sync(0xffffffffu, last, 2);
  if (lane == 0) kq[640] = 2.f * last;
  __syncwarp();
  uint32_t* kr = reinterpret_cast<uint32_t*>(g_kr + d * KCH);
  uint32_t* kr2 = reinterpret_cast<uint32_t*>(g_kr + d * KCH + KSZ + 16);
#pragma unroll 4
  for (int w = lane; w < KSZ / 2; w += 32) {
    float kv[3];
#pragma unroll
    for (int q = 0; q < 3; q++) {
      const int xk = KOFF - 2 * w - q;
      float val = 0.f;
      if (xk >= 0 && xk < SEQ) {
        const uint32_t pb = __float_as_uint(bfr((float)xk));
        const int id = xk < 256 ? xk : (256 + ((int)(pb >> 23) - 135) * 128 + (int)((pb >> 16) & 127));
        val = __ldcg(kq + id);
      }
      kv[q] = val;
    }
    kr[w] = pack2(kv[0], kv[1]);
    kr2[w] = pack2(kv[1], kv[2]);
  }
  if (lane < 8) kr[KSZ / 2 + lane] = 0u;
}

__global__ void __launch_bounds__(256)
k0_kgen(const bf16* __restrict__ x, const bf16* __restrict__ logAr, const bf16* __restrict__ Aim, const bf16* __restrict__ Cre,
        const bf16* __restrict__ Cim, const bf16* __restrict__ logdt, const bf16* __restrict__ gatew) {
  const int warp = threadIdx.x >> 5, lane = threadIdx.x & 31;
  for (int rr = 0; rr < 2; rr++) {
    const int r = blockIdx.x * 16 + warp * 2 + rr;
    float s = 0.f;
    for (int c = lane * 8; c < DM; c += 256) {
      uint4 xv = *reinterpret_cast<const uint4*>(x + (size_t)r * DM + c);
      uint4 wv = *reinterpret_cast<const uint4*>(gatew + c);
      const bf16* xp = reinterpret_cast<const bf16*>(&xv);
      const bf16* wp = reinterpret_cast<const bf16*>(&wv);
#pragma unroll
      for (int q = 0; q < 8; q++) s += bfr(__bfloat162float(xp[q]) * __bfloat162float(wp[q]));
    }
#pragma unroll
    for (int o = 16; o; o >>= 1) s += __shfl_xor_sync(0xffffffffu, s, o);
    if (lane == 0) { float z = bfr(s); g_gate[r] = bfr(1.0f / (1.0f + expf(-z))); }
  }
  kgen_channel(blockIdx.x * 8 + warp, lane, logAr, Aim, Cre, Cim, logdt);
}

namespace k2 {
constexpr int CH = 8;
constexpr int UPAD = 128;
constexpr int USZ = UPAD + SEQ;
constexpr int OFF_U = 0;
constexpr int OFF_K = OFF_U + CH * USZ * 2;
constexpr int OFF_R = OFF_K + CH * KCH * 2;
constexpr int OFF_BAR = OFF_R + CH * SEQ * 4;
constexpr int SMEM = OFF_BAR + 16;
}

__global__ void __launch_bounds__(512, 1)
k2_conv(const bf16* __restrict__ x, const bf16* __restrict__ Dskip) {
  using namespace k2;
  extern __shared__ __align__(16) uint8_t sm[];
  const int tid = threadIdx.x, warp = tid >> 5, lane = tid & 31, g = lane >> 2, t = lane & 3;
  const int ch = warp >> 1, half = warp & 1;
  const int d0 = blockIdx.x * CH;
  bf16* us = reinterpret_cast<bf16*>(sm + OFF_U);
  bf16* ks = reinterpret_cast<bf16*>(sm + OFF_K);
  const uint32_t bar = smem_u32(sm + OFF_BAR);

  if (tid == 0) {
    mbar_init(bar, 1);
    asm volatile("fence.mbarrier_init.release.cluster;" ::: "memory");
    mbar_expect_tx(bar, CH * KCH * 2);
    asm volatile("cp.async.bulk.shared::cluster.global.mbarrier::complete_tx::bytes [%0], [%1], %2, [%3];" ::"r"(smem_u32(ks)),
                 "l"(g_kr + (size_t)d0 * KCH), "r"(CH * KCH * 2), "r"(bar) : "memory");
  }
  if (tid < CH * UPAD / 2) {
    const int c = tid / (UPAD / 2), o = tid % (UPAD / 2);
    reinterpret_cast<uint32_t*>(us + c * USZ)[o] = 0u;
  }
  {
    uint4 v[2][2];
#pragma unroll
    for (int it = 0; it < 2; it++) {
      const int l = 2 * (tid + it * 512);
      v[it][0] = __ldg(reinterpret_cast<const uint4*>(x + (size_t)l * DM + d0));
      v[it][1] = __ldg(reinterpret_cast<const uint4*>(x + (size_t)(l + 1) * DM + d0));
    }
#pragma unroll
    for (int it = 0; it < 2; it++) {
      const int l = 2 * (tid + it * 512);
      const int e = l & 15;
      const int pe = ((e & 7) >> 1) * 4 + (e >> 3) * 2;
      const int pos = UPAD + (l & ~15) + pe;
      const uint32_t a[4] = {v[it][0].x, v[it][0].y, v[it][0].z, v[it][0].w};
      const uint32_t b[4] = {v[it][1].x, v[it][1].y, v[it][1].z, v[it][1].w};
#pragma unroll
      for (int c = 0; c < 4; c++) {
        *reinterpret_cast<uint32_t*>(us + (2 * c) * USZ + pos) = __byte_perm(a[c], b[c], 0x5410);
        *reinterpret_cast<uint32_t*>(us + (2 * c + 1) * USZ + pos) = __byte_perm(a[c], b[c], 0x7632);
      }
    }
  }
  __syncthreads();
  mbar_wait(bar, 0);

  float D[16][4];
#pragma unroll
  for (int j = 0; j < 16; j++)
#pragma unroll
    for (int q = 0; q < 4; q++) D[j][q] = 0.f;
  const bf16* uc = us + ch * USZ + UPAD;
  {
    const bf16* kr = ks + ch * KCH;
    const uint32_t* fbase = reinterpret_cast<const uint32_t*>((g & 1) ? (kr + KSZ + 16) : kr) + ((KOFF - g + 2 * t) >> 1);
    for (int r = half * 4; r < half * 4 + 4; r++) {
      uint32_t B[16][2];
#pragma unroll
      for (int j = 0; j < 16; j++) {
        const uint2 v = *reinterpret_cast<const uint2*>(uc + 16 * (8 * j - r + g) + 4 * t);
        B[j][0] = v.x; B[j][1] = v.y;
      }
      uint32_t fm1 = fbase[-4 * (2 * r - 1)];
#pragma unroll
      for (int k = 0; k < 16; k++) {
        const int dl = 8 * k + r;
        const uint32_t f0 = fbase[-4 * (2 * dl)];
        const uint32_t f1 = fbase[-4 * (2 * dl + 1)];
        if (k > 0) fm1 = fbase[-4 * (2 * dl - 1)];
#pragma unroll
        for (int j = k; j < 16; j++) mma_bf16(D[j], f0, f1, fm1, f0, B[j - k][0], B[j - k][1]);
      }
    }
  }
  float* red = reinterpret_cast<float*>(sm + OFF_R) + ch * SEQ;
#pragma unroll
  for (int j = 0; j < 8; j++) {
    const int jo = half ? j : j + 8;
    *reinterpret_cast<float4*>(red + (jo * 32 + lane) * 4) =
        make_float4(half ? D[j][0] : D[j + 8][0], half ? D[j][1] : D[j + 8][1], half ? D[j][2] : D[j + 8][2], half ? D[j][3] : D[j + 8][3]);
  }
  named_bar_sync(1 + ch, 64);
  {
    const float dsk = __bfloat162float(Dskip[d0 + ch]);
    uint32_t outp[8][2];
#pragma unroll
    for (int j = 0; j < 8; j++) {
      const int jm = half ? j + 8 : j;
      const float4 o = *reinterpret_cast<const float4*>(red + (jm * 32 + lane) * 4);
      const float dd[4] = {(half ? D[j + 8][0] : D[j][0]) + o.x, (half ? D[j + 8][1] : D[j][1]) + o.y,
                           (half ? D[j + 8][2] : D[j][2]) + o.z, (half ? D[j + 8][3] : D[j][3]) + o.w};
      float y[4];
#pragma unroll
      for (int q = 0; q < 4; q++) {
        const int a = 8 * jm + 2 * t + (q & 1), bb = g + (q >> 1) * 8;
        const int pe = ((bb & 7) >> 1) * 4 + (bb >> 3) * 2 + (bb & 1);
        const float uv = __bfloat162float(uc[16 * a + pe]);
        y[q] = bfr(dd[q]) + bfr(uv * dsk);
      }
      outp[j][0] = pack2(y[0], y[1]);
      outp[j][1] = pack2(y[2], y[3]);
    }
    named_bar_sync(1 + ch, 64);
    bf16* ys = reinterpret_cast<bf16*>(red);
#pragma unroll
    for (int j = 0; j < 8; j++) {
      const int jm = half ? j + 8 : j;
      const int a = 8 * jm + 2 * t;
      const uint32_t p0 = outp[j][0], p1 = outp[j][1];
      reinterpret_cast<uint16_t*>(ys)[16 * a + g] = (uint16_t)(p0 & 0xffff);
      reinterpret_cast<uint16_t*>(ys)[16 * (a + 1) + g] = (uint16_t)(p0 >> 16);
      reinterpret_cast<uint16_t*>(ys)[16 * a + g + 8] = (uint16_t)(p1 & 0xffff);
      reinterpret_cast<uint16_t*>(ys)[16 * (a + 1) + g + 8] = (uint16_t)(p1 >> 16);
    }
    __syncwarp();
    bf16* dst = g_bT + (size_t)(d0 + ch) * SEQ + half * 1024;
#pragma unroll
    for (int i = 0; i < 4; i++) {
      const uint4 v = *reinterpret_cast<const uint4*>(ys + half * 1024 + (i * 32 + lane) * 8);
      *reinterpret_cast<uint4*>(dst + (i * 32 + lane) * 8) = v;
    }
  }
}

typedef CUresult (*EncodeFn)(CUtensorMap*, CUtensorMapDataType, cuuint32_t, void*, const cuuint64_t*, const cuuint64_t*,
                             const cuuint32_t*, const cuuint32_t*, CUtensorMapInterleave, CUtensorMapSwizzle,
                             CUtensorMapL2promotion, CUtensorMapFloatOOBfill);

static void make_map(EncodeFn enc, CUtensorMap* m, void* ptr, uint64_t inner, uint64_t outer, uint32_t bi, uint32_t bo) {
  cuuint64_t dims[2] = {inner, outer};
  cuuint64_t strides[1] = {inner * 2};
  cuuint32_t box[2] = {bi, bo};
  cuuint32_t es[2] = {1, 1};
  enc(m, CU_TENSOR_MAP_DATA_TYPE_BFLOAT16, 2, ptr, dims, strides, box, es, CU_TENSOR_MAP_INTERLEAVE_NONE,
      CU_TENSOR_MAP_SWIZZLE_128B, CU_TENSOR_MAP_L2_PROMOTION_L2_256B, CU_TENSOR_MAP_FLOAT_OOB_FILL_NONE);
}

extern "C" void kernel_launch(void* const* d_in, const int* in_sizes, int n_in, void* d_out, int out_size) {
  const bf16* x = (const bf16*)d_in[0];
  const bf16* wqkv = (const bf16*)d_in[1];
  const bf16* wo = (const bf16*)d_in[2];
  const bf16* logAr = (const bf16*)d_in[4];
  const bf16* Aim = (const bf16*)d_in[5];
  const bf16* Cre = (const bf16*)d_in[6];
  const bf16* Cim = (const bf16*)d_in[7];
  const bf16* logdt = (const bf16*)d_in[8];
  const bf16* Dskip = (const bf16*)d_in[9];
  const bf16* gatew = (const bf16*)d_in[10];

  static EncodeFn enc = nullptr;
  static void* p_o = nullptr;
  static void* p_bT = nullptr;
  if (!enc) {
    void* fn = nullptr;
    cudaDriverEntryPointQueryResult qr;
    cudaGetDriverEntryPoint("cuTensorMapEncodeTiled", &fn, cudaEnableDefault, &qr);
    enc = (EncodeFn)fn;
    cudaGetSymbolAddress(&p_o, g_o);
    cudaGetSymbolAddress(&p_bT, g_bT);
    cudaFuncSetAttribute(k1_qkv_attn, cudaFuncAttributeMaxDynamicSharedMemorySize, k1::SMEM);
    cudaFuncSetAttribute(k2_conv, cudaFuncAttributeMaxDynamicSharedMemorySize, k2::SMEM);
    cudaFuncSetAttribute(k3_out, cudaFuncAttributeMaxDynamicSharedMemorySize, k3::SMEM);
  }
  CUtensorMap tmx, tmw, tmo, tmwo, tmbt, tmout;
  make_map(enc, &tmx, (void*)x, 1024, 2048, 64, 128);
  make_map(enc, &tmw, (void*)wqkv, 3072, 1024, 64, 64);
  make_map(enc, &tmo, p_o, 1024, 2048, 64, 64);
  make_map(enc, &tmwo, (void*)wo, 1024, 1024, 64, 64);
  make_map(enc, &tmbt, p_bT, 2048, 1024, 64, 128);
  make_map(enc, &tmout, d_out, 1024, 2048, 64, 64);

  k0_kgen<<<128, 256>>>(x, logAr, Aim, Cre, Cim, logdt, gatew);
  k2_conv<<<128, 512, k2::SMEM>>>(x, Dskip);
  k1_qkv_attn<<<128, 384, k1::SMEM>>>(tmx, tmw);
  k3_out<<<128, 384, k3::SMEM>>>(tmo, tmwo, tmbt, tmout);
}
```

```cpp
#include <cuda_runtime.h>
#include <cuda_bf16.h>
#include <cuda.h>
#include <stdint.h>

typedef __nv_bfloat16 bf16;

constexpr int SEQ = 2048, DM = 1024, NMODE = 128;

__device__ __align__(1024) bf16 g_o[SEQ * DM];
__device__ __align__(1024) bf16 g_b[SEQ * DM];
__device__ float g_gate[SEQ];
__device__ __align__(16) float g_part[16 * 8 * 2 * 1056];
__device__ unsigned int g_cnt[16];

__device__ __forceinline__ uint32_t smem_u32(const void* p) { return (uint32_t)__cvta_generic_to_shared(p); }
__device__ __forceinline__ void mbar_init(uint32_t bar, uint32_t cnt) {
  asm volatile("mbarrier.init.shared::cta.b64 [%0], %1;" ::"r"(bar), "r"(cnt));
}
__device__ __forceinline__ void mbar_expect_tx(uint32_t bar, uint32_t bytes) {
  asm volatile("mbarrier.arrive.expect_tx.shared::cta.b64 _, [%0], %1;" ::"r"(bar), "r"(bytes) : "memory");
}
__device__ __forceinline__ void mbar_arrive_cluster(uint32_t bar, uint32_t cta) {
  asm volatile(
      "{\n.reg .b32 ra;\nmapa.shared::cluster.u32 ra, %0, %1;\n"
      "mbarrier.arrive.shared::cluster.b64 _, [ra];\n}\n" ::"r"(bar), "r"(cta) : "memory");
}
__device__ __forceinline__ bool mbar_try_wait(uint32_t bar, uint32_t parity) {
  uint32_t ok;
  asm volatile(
      "{\n.reg .pred p;\nmbarrier.try_wait.parity.shared::cta.b64 p, [%1], %2;\nselp.u32 %0, 1, 0, p;\n}\n"
      : "=r"(ok) : "r"(bar), "r"(parity) : "memory");
  return ok;
}
__device__ __forceinline__ void mbar_wait(uint32_t bar, uint32_t parity) {
  while (!mbar_try_wait(bar, parity)) {}
}
__device__ __forceinline__ void tma_load_2d(uint32_t dst, const CUtensorMap* map, uint32_t bar, int c0, int c1) {
  asm volatile(
      "cp.async.bulk.tensor.2d.shared::cluster.global.mbarrier::complete_tx::bytes [%0], [%1, {%3, %4}], [%2];" ::"r"(dst),
      "l"(map), "r"(bar), "r"(c0), "r"(c1) : "memory");
}
__device__ __forceinline__ void tma_load_2d_mc(uint32_t dst, const CUtensorMap* map, uint32_t bar, int c0, int c1,
                                               uint16_t mask) {
  asm volatile(
      "cp.async.bulk.tensor.2d.shared::cluster.global.mbarrier::complete_tx::bytes.multicast::cluster [%0], [%1, {%3, %4}], [%2], %5;" ::"r"(dst),
      "l"(map), "r"(bar), "r"(c0), "r"(c1), "h"(mask) : "memory");
}
__device__ __forceinline__ void cluster_sync_all() {
  asm volatile("barrier.cluster.arrive.release.aligned;\nbarrier.cluster.wait.acquire.aligned;\n" ::: "memory");
}
__device__ __forceinline__ uint32_t cluster_ctarank() {
  uint32_t r; asm volatile("mov.u32 %0, %%cluster_ctarank;" : "=r"(r)); return r;
}
__device__ __forceinline__ void named_bar_sync(int id, int n) { asm volatile("bar.sync %0, %1;" ::"r"(id), "r"(n) : "memory"); }
__device__ __forceinline__ void fence_async_smem() { asm volatile("fence.proxy.async.shared::cta;" ::: "memory"); }
__device__ __forceinline__ void wg_fence() { asm volatile("wgmma.fence.sync.aligned;" ::: "memory"); }
__device__ __forceinline__ void wg_commit() { asm volatile("wgmma.commit_group.sync.aligned;" ::: "memory"); }
template <int N> __device__ __forceinline__ void wg_wait() { asm volatile("wgmma.wait_group.sync.aligned %0;" ::"n"(N) : "memory"); }
__device__ __forceinline__ uint64_t make_desc(uint32_t addr, uint32_t lbo, uint32_t sbo) {
  return (uint64_t)((addr & 0x3FFFF) >> 4) | ((uint64_t)(lbo >> 4) << 16) | ((uint64_t)(sbo >> 4) << 32) | (1ull << 62);
}
__device__ __forceinline__ float bfr(float x) { return __bfloat162float(__float2bfloat16_rn(x)); }
__device__ __forceinline__ uint32_t pack2(float lo, float hi) {
  __nv_bfloat162 v = __floats2bfloat162_rn(lo, hi);
  return *reinterpret_cast<uint32_t*>(&v);
}
__device__ __forceinline__ float ex2f(float x) { float r; asm("ex2.approx.ftz.f32 %0, %1;" : "=f"(r) : "f"(x)); return r; }
__device__ __forceinline__ float lo_f(uint32_t v) { return __uint_as_float(v << 16); }
__device__ __forceinline__ float hi_f(uint32_t v) { return __uint_as_float(v & 0xffff0000u); }
__device__ __forceinline__ uint32_t phi2(float a0, float a1) {
  const uint32_t t2 = pack2(a0, a1);
  const float t0 = lo_f(t2), t1 = hi_f(t2);
  const float e0 = ex2f(t0 * 1.4426950408889634f), e1 = ex2f(t1 * 1.4426950408889634f);
  const float f0 = t0 > 0.f ? t0 + 1.0f : e0;
  const float f1 = t1 > 0.f ? t1 + 1.0f : e1;
  const uint32_t f2 = pack2(f0, f1);
  return pack2(lo_f(f2) + 1e-6f, hi_f(f2) + 1e-6f);
}
template <int R> __device__ __forceinline__ void fence_regs(float (&d)[R]) {
#pragma unroll
  for (int i = 0; i < R; i++) asm volatile("" : "+f"(d[i])::"memory");
}

__device__ __forceinline__ void wgmma_ss_n192_tb(float (&d)[96], uint64_t da, uint64_t db, int sc) {
  asm volatile("{\n.reg .pred p;\nsetp.ne.b32 p, %98, 0;\n"
    "wgmma.mma_async.sync.aligned.m64n192k16.f32.bf16.bf16 {%0, %1, %2, %3, %4, %5, %6, %7, %8, %9, %10, %11, %12, %13, %14, %15, %16, %17, %18, %19, %20, %21, %22, %23, %24, %25, %26, %27, %28, %29, %30, %31, %32, %33, %34, %35, %36, %37, %38, %39, %40, %41, %42, %43, %44, %45, %46, %47, %48, %49, %50, %51, %52, %53, %54, %55, %56, %57, %58, %59, %60, %61, %62, %63, %64, %65, %66, %67, %68, %69, %70, %71, %72, %73, %74, %75, %76, %77, %78, %79, %80, %81, %82, %83, %84, %85, %86, %87, %88, %89, %90, %91, %92, %93, %94, %95}, %96, %97, p, 1, 1, 0, 1;\n}\n"
    : "+f"(d[0]), "+f"(d[1]), "+f"(d[2]), "+f"(d[3]), "+f"(d[4]), "+f"(d[5]), "+f"(d[6]), "+f"(d[7]), "+f"(d[8]), "+f"(d[9]), "+f"(d[10]), "+f"(d[11]), "+f"(d[12]), "+f"(d[13]), "+f"(d[14]), "+f"(d[15]), "+f"(d[16]), "+f"(d[17]), "+f"(d[18]), "+f"(d[19]), "+f"(d[20]), "+f"(d[21]), "+f"(d[22]), "+f"(d[23]), "+f"(d[24]), "+f"(d[25]), "+f"(d[26]), "+f"(d[27]), "+f"(d[28]), "+f"(d[29]), "+f"(d[30]), "+f"(d[31]), "+f"(d[32]), "+f"(d[33]), "+f"(d[34]), "+f"(d[35]), "+f"(d[36]), "+f"(d[37]), "+f"(d[38]), "+f"(d[39]), "+f"(d[40]), "+f"(d[41]), "+f"(d[42]), "+f"(d[43]), "+f"(d[44]), "+f"(d[45]), "+f"(d[46]), "+f"(d[47]), "+f"(d[48]), "+f"(d[49]), "+f"(d[50]), "+f"(d[51]), "+f"(d[52]), "+f"(d[53]), "+f"(d[54]), "+f"(d[55]), "+f"(d[56]), "+f"(d[57]), "+f"(d[58]), "+f"(d[59]), "+f"(d[60]), "+f"(d[61]), "+f"(d[62]), "+f"(d[63]), "+f"(d[64]), "+f"(d[65]), "+f"(d[66]), "+f"(d[67]), "+f"(d[68]), "+f"(d[69]), "+f"(d[70]), "+f"(d[71]), "+f"(d[72]), "+f"(d[73]), "+f"(d[74]), "+f"(d[75]), "+f"(d[76]), "+f"(d[77]), "+f"(d[78]), "+f"(d[79]), "+f"(d[80]), "+f"(d[81]), "+f"(d[82]), "+f"(d[83]), "+f"(d[84]), "+f"(d[85]), "+f"(d[86]), "+f"(d[87]), "+f"(d[88]), "+f"(d[89]), "+f"(d[90]), "+f"(d[91]), "+f"(d[92]), "+f"(d[93]), "+f"(d[94]), "+f"(d[95])
    : "l"(da), "l"(db), "r"(sc));
}

__device__ __forceinline__ void wgmma_ss_n128_tb(float (&d)[64], uint64_t da, uint64_t db, int sc) {
  asm volatile("{\n.reg .pred p;\nsetp.ne.b32 p, %66, 0;\n"
    "wgmma.mma_async.sync.aligned.m64n128k16.f32.bf16.bf16 {%0, %1, %2, %3, %4, %5, %6, %7, %8, %9, %10, %11, %12, %13, %14, %15, %16, %17, %18, %19, %20, %21, %22, %23, %24, %25, %26, %27, %28, %29, %30, %31, %32, %33, %34, %35, %36, %37, %38, %39, %40, %41, %42, %43, %44, %45, %46, %47, %48, %49, %50, %51, %52, %53, %54, %55, %56, %57, %58, %59, %60, %61, %62, %63}, %64, %65, p, 1, 1, 0, 1;\n}\n"
    : "+f"(d[0]), "+f"(d[1]), "+f"(d[2]), "+f"(d[3]), "+f"(d[4]), "+f"(d[5]), "+f"(d[6]), "+f"(d[7]), "+f"(d[8]), "+f"(d[9]), "+f"(d[10]), "+f"(d[11]), "+f"(d[12]), "+f"(d[13]), "+f"(d[14]), "+f"(d[15]), "+f"(d[16]), "+f"(d[17]), "+f"(d[18]), "+f"(d[19]), "+f"(d[20]), "+f"(d[21]), "+f"(d[22]), "+f"(d[23]), "+f"(d[24]), "+f"(d[25]), "+f"(d[26]), "+f"(d[27]), "+f"(d[28]), "+f"(d[29]), "+f"(d[30]), "+f"(d[31]), "+f"(d[32]), "+f"(d[33]), "+f"(d[34]), "+f"(d[35]), "+f"(d[36]), "+f"(d[37]), "+f"(d[38]), "+f"(d[39]), "+f"(d[40]), "+f"(d[41]), "+f"(d[42]), "+f"(d[43]), "+f"(d[44]), "+f"(d[45]), "+f"(d[46]), "+f"(d[47]), "+f"(d[48]), "+f"(d[49]), "+f"(d[50]), "+f"(d[51]), "+f"(d[52]), "+f"(d[53]), "+f"(d[54]), "+f"(d[55]), "+f"(d[56]), "+f"(d[57]), "+f"(d[58]), "+f"(d[59]), "+f"(d[60]), "+f"(d[61]), "+f"(d[62]), "+f"(d[63])
    : "l"(da), "l"(db), "r"(sc));
}

__device__ __forceinline__ void wgmma_ss_n64_tatb(float (&d)[32], uint64_t da, uint64_t db, int sc) {
  asm volatile("{\n.reg .pred p;\nsetp.ne.b32 p, %34, 0;\n"
    "wgmma.mma_async.sync.aligned.m64n64k16.f32.bf16.bf16 {%0, %1, %2, %3, %4, %5, %6, %7, %8, %9, %10, %11, %12, %13, %14, %15, %16, %17, %18, %19, %20, %21, %22, %23, %24, %25, %26, %27, %28, %29, %30, %31}, %32, %33, p, 1, 1, 1, 1;\n}\n"
    : "+f"(d[0]), "+f"(d[1]), "+f"(d[2]), "+f"(d[3]), "+f"(d[4]), "+f"(d[5]), "+f"(d[6]), "+f"(d[7]), "+f"(d[8]), "+f"(d[9]), "+f"(d[10]), "+f"(d[11]), "+f"(d[12]), "+f"(d[13]), "+f"(d[14]), "+f"(d[15]), "+f"(d[16]), "+f"(d[17]), "+f"(d[18]), "+f"(d[19]), "+f"(d[20]), "+f"(d[21]), "+f"(d[22]), "+f"(d[23]), "+f"(d[24]), "+f"(d[25]), "+f"(d[26]), "+f"(d[27]), "+f"(d[28]), "+f"(d[29]), "+f"(d[30]), "+f"(d[31])
    : "l"(da), "l"(db), "r"(sc));
}

__device__ __forceinline__ void wgmma_ss_n8_tatb(float (&d)[4], uint64_t da, uint64_t db, int sc) {
  asm volatile("{\n.reg .pred p;\nsetp.ne.b32 p, %6, 0;\n"
    "wgmma.mma_async.sync.aligned.m64n8k16.f32.bf16.bf16 {%0, %1, %2, %3}, %4, %5, p, 1, 1, 1, 1;\n}\n"
    : "+f"(d[0]), "+f"(d[1]), "+f"(d[2]), "+f"(d[3])
    : "l"(da), "l"(db), "r"(sc));
}

__device__ __forceinline__ void wgmma_rs_n40_tb(float (&d)[20], uint32_t a0, uint32_t a1, uint32_t a2, uint32_t a3, uint64_t db, int sc) {
  asm volatile("{\n.reg .pred p;\nsetp.ne.b32 p, %25, 0;\n"
    "wgmma.mma_async.sync.aligned.m64n40k16.f32.bf16.bf16 {%0, %1, %2, %3, %4, %5, %6, %7, %8, %9, %10, %11, %12, %13, %14, %15, %16, %17, %18, %19}, {%20, %21, %22, %23}, %24, p, 1, 1, 1;\n}\n"
    : "+f"(d[0]), "+f"(d[1]), "+f"(d[2]), "+f"(d[3]), "+f"(d[4]), "+f"(d[5]), "+f"(d[6]), "+f"(d[7]), "+f"(d[8]), "+f"(d[9]), "+f"(d[10]), "+f"(d[11]), "+f"(d[12]), "+f"(d[13]), "+f"(d[14]), "+f"(d[15]), "+f"(d[16]), "+f"(d[17]), "+f"(d[18]), "+f"(d[19])
    : "r"(a0), "r"(a1), "r"(a2), "r"(a3), "l"(db), "r"(sc));
}


namespace k1 {
constexpr int BM = 256, BN = 192, BK = 64, ST = 4;
constexpr int A_BYTES = BM * BK * 2, B_BYTES = BK * BN * 2, STAGE = A_BYTES + B_BYTES;
constexpr int SMEM = ST * STAGE + 1024 + 256;
constexpr int OFF_PK = 0, OFF_V = 32768, OFF_ONES = 65536, OFF_KV = 69632, OFF_O = 81920, OFF_RED = 114688;
}

__global__ void __cluster_dims__(2, 1, 1) __launch_bounds__(384, 1)
k1_qkv_attn(const __grid_constant__ CUtensorMap tmx, const __grid_constant__ CUtensorMap tmw) {
  using namespace k1;
  extern __shared__ uint8_t smem_raw[];
  const uint32_t sbase = (smem_u32(smem_raw) + 1023) & ~1023u;
  uint8_t* sgen = smem_raw + (sbase - smem_u32(smem_raw));
  const uint32_t bars = sbase + ST * STAGE;
  const int tid = threadIdx.x, warp = tid >> 5, lane = tid & 31;
  const uint32_t rank = cluster_ctarank();
  const int cl = blockIdx.x >> 1;
  const int mt = cl >> 3;
  const int hp = ((cl & 7) << 1) + rank;
  const int m0 = mt * BM;

  if (tid == 0) {
    for (int s = 0; s < ST; s++) {
      mbar_init(bars + 8 * s, 1);
      mbar_init(bars + 8 * (ST + s), 16);
    }
    asm volatile("fence.mbarrier_init.release.cluster;" ::: "memory");
  }
  cluster_sync_all();

  if (warp >= 8) {
    asm volatile("setmaxnreg.dec.sync.aligned.u32 40;");
    if (warp == 8 && lane == 0) {
      for (int kb = 0; kb < DM / BK; kb++) {
        const int s = kb % ST;
        mbar_wait(bars + 8 * (ST + s), ((kb / ST) & 1) ^ 1);
        const uint32_t full = bars + 8 * s;
        mbar_expect_tx(full, STAGE);
        const uint32_t sa = sbase + s * STAGE, sb = sa + A_BYTES;
        tma_load_2d_mc(sa + rank * 16384, &tmx, full, kb * BK, m0 + rank * 128, (uint16_t)3);
#pragma unroll
        for (int j = 0; j < 3; j++) tma_load_2d(sb + j * 8192, &tmw, full, j * 1024 + hp * 64, kb * BK);
      }
    }
    cluster_sync_all();
  } else {
    asm volatile("setmaxnreg.inc.sync.aligned.u32 232;");
    const int wg = warp >> 2, w4 = warp & 3, g = lane >> 2, t = lane & 3;
    float acc[2][96];
#pragma unroll
    for (int i = 0; i < 96; i++) { acc[0][i] = 0.f; acc[1][i] = 0.f; }
    for (int kb = 0; kb < DM / BK; kb++) {
      const int s = kb % ST;
      mbar_wait(bars + 8 * s, (kb / ST) & 1);
      const uint32_t sa = sbase + s * STAGE + wg * 16384, sb = sbase + s * STAGE + A_BYTES;
      wg_fence();
#pragma unroll
      for (int ks = 0; ks < 4; ks++) {
        const uint64_t db = make_desc(sb + ks * 2048, 8192, 1024);
#pragma unroll
        for (int mb = 0; mb < 2; mb++) {
          const uint64_t da = make_desc(sa + mb * 8192 + ks * 32, 16, 1024);
          wgmma_ss_n192_tb(acc[mb], da, db, 1);
        }
      }
      wg_commit();
      if (kb > 0) {
        wg_wait<1>();
        const int sp = (kb - 1) % ST;
        if (lane == 0) { mbar_arrive_cluster(bars + 8 * (ST + sp), 0); mbar_arrive_cluster(bars + 8 * (ST + sp), 1); }
      }
    }
    wg_wait<0>();
    fence_regs(acc[0]); fence_regs(acc[1]);
    named_bar_sync(1, 256);

#pragma unroll
    for (int mb = 0; mb < 2; mb++) {
#pragma unroll
      for (int h = 0; h < 2; h++) {
        const int r = wg * 128 + mb * 64 + w4 * 16 + g + h * 8;
#pragma unroll
        for (int j = 0; j < 8; j++) {
          const uint32_t off = r * 128 + ((j ^ (r & 7)) << 4) + t * 4;
          const float k0 = acc[mb][4 * (8 + j) + 2 * h], k1v = acc[mb][4 * (8 + j) + 2 * h + 1];
          const float v0 = acc[mb][4 * (16 + j) + 2 * h], v1 = acc[mb][4 * (16 + j) + 2 * h + 1];
          *reinterpret_cast<uint32_t*>(sgen + OFF_PK + off) = phi2(k0, k1v);
          *reinterpret_cast<uint32_t*>(sgen + OFF_V + off) = pack2(v0, v1);
        }
      }
    }
    if (tid < 256) *reinterpret_cast<uint32_t*>(sgen + OFF_ONES + tid * 4) = 0x3F803F80u;
    fence_async_smem();
    named_bar_sync(1, 256);

    float* part = g_part + (size_t)(hp * 8 + mt) * 2112;
    {
      float kv[32], zz[4];
#pragma unroll
      for (int i = 0; i < 32; i++) kv[i] = 0.f;
#pragma unroll
      for (int i = 0; i < 4; i++) zz[i] = 0.f;
      wg_fence();
#pragma unroll
      for (int ks = 0; ks < 8; ks++) {
        const uint64_t da = make_desc(sbase + OFF_PK + wg * 16384 + ks * 2048, 16, 1024);
        const uint64_t db = make_desc(sbase + OFF_V + wg * 16384 + ks * 2048, 16, 1024);
        const uint64_t d1 = make_desc(sbase + OFF_ONES, 16, 0);
        wgmma_ss_n64_tatb(kv, da, db, 1);
        wgmma_ss_n8_tatb(zz, da, d1, 1);
      }
      wg_commit();
      wg_wait<0>();
      fence_regs(kv); fence_regs(zz);
      const int hh = w4 >> 1;
      float* red = reinterpret_cast<float*>(sgen + OFF_RED);
      float vals[2][4][2];
#pragma unroll
      for (int h = 0; h < 2; h++)
#pragma unroll
        for (int j = 0; j < 4; j++) {
          vals[h][j][0] = hh ? kv[4 * (4 + j) + 2 * h] : kv[4 * j + 2 * h];
          vals[h][j][1] = hh ? kv[4 * (4 + j) + 2 * h + 1] : kv[4 * j + 2 * h + 1];
        }
      if (wg == 1) {
#pragma unroll
        for (int h = 0; h < 2; h++) {
          const int d = (w4 & 1) * 16 + g + h * 8;
#pragma unroll
          for (int j = 0; j < 4; j++)
            *reinterpret_cast<float2*>(red + hh * 1056 + d * 32 + 8 * j + 2 * t) = make_float2(vals[h][j][0], vals[h][j][1]);
          if (t == 0) red[hh * 1056 + 1024 + d] = zz[2 * h];
        }
      }
      named_bar_sync(1, 256);
      if (wg == 0) {
#pragma unroll
        for (int h = 0; h < 2; h++) {
          const int d = (w4 & 1) * 16 + g + h * 8;
#pragma unroll
          for (int j = 0; j < 4; j++) {
            const float2 o = *reinterpret_cast<const float2*>(red + hh * 1056 + d * 32 + 8 * j + 2 * t);
            *reinterpret_cast<float2*>(part + hh * 1056 + d * 32 + 8 * j + 2 * t) = make_float2(vals[h][j][0] + o.x, vals[h][j][1] + o.y);
          }
          if (t == 0) part[hh * 1056 + 1024 + d] = zz[2 * h] + red[hh * 1056 + 1024 + d];
        }
        __threadfence();
        named_bar_sync(2, 128);
        if (tid == 0) atomicAdd(&g_cnt[hp], 1u);
      }
    }
    uint32_t pq[2][4][4];
#pragma unroll
    for (int mb = 0; mb < 2; mb++)
#pragma unroll
      for (int kk = 0; kk < 4; kk++) {
        pq[mb][kk][0] = phi2(acc[mb][8 * kk + 0], acc[mb][8 * kk + 1]);
        pq[mb][kk][1] = phi2(acc[mb][8 * kk + 2], acc[mb][8 * kk + 3]);
        pq[mb][kk][2] = phi2(acc[mb][8 * kk + 4], acc[mb][8 * kk + 5]);
        pq[mb][kk][3] = phi2(acc[mb][8 * kk + 6], acc[mb][8 * kk + 7]);
      }
    if (tid == 0) {
      unsigned int v;
      do { asm volatile("ld.acquire.gpu.global.u32 %0, [%1];" : "=r"(v) : "l"(&g_cnt[hp]) : "memory"); } while (v < 8u);
    }
    named_bar_sync(1, 256);
    {
      const float* pb = g_part + (size_t)(hp * 8) * 2112;
      for (int i = tid; i < 528; i += 256) {
        float4 s4 = make_float4(0.f, 0.f, 0.f, 0.f);
#pragma unroll
        for (int p = 0; p < 8; p++) {
          float4 v4 = __ldcg(reinterpret_cast<const float4*>(pb + p * 2112) + i);
          s4.x += v4.x; s4.y += v4.y; s4.z += v4.z; s4.w += v4.w;
        }
        const int hh = i / 264, rem = i - hh * 264;
        uint8_t* tile = sgen + OFF_KV + hh * 4096;
        if (rem < 256) {
          const int d = rem >> 3, e = (rem & 7) * 4;
          const uint32_t off = d * 128 + (((e >> 3) ^ (d & 7)) << 4) + (e & 7) * 2;
          *reinterpret_cast<uint2*>(tile + off) = make_uint2(pack2(s4.x, s4.y), pack2(s4.z, s4.w));
        } else {
          const int d0 = (rem - 256) * 4;
          float zv[4] = {s4.x, s4.y, s4.z, s4.w};
#pragma unroll
          for (int q = 0; q < 4; q++) {
            const int d = d0 + q;
            const uint32_t off = d * 128 + ((4 ^ (d & 7)) << 4);
            *reinterpret_cast<uint4*>(tile + off) = make_uint4(pack2(zv[q], 0.f), 0u, 0u, 0u);
          }
        }
      }
    }
    fence_async_smem();
    named_bar_sync(1, 256);
#pragma unroll
    for (int mb = 0; mb < 2; mb++) {
#pragma unroll
      for (int hh = 0; hh < 2; hh++) {
        float num[20];
#pragma unroll
        for (int i = 0; i < 20; i++) num[i] = 0.f;
        wg_fence();
#pragma unroll
        for (int kk = 0; kk < 2; kk++) {
          const uint64_t db = make_desc(sbase + OFF_KV + hh * 4096 + kk * 2048, 16, 1024);
          wgmma_rs_n40_tb(num, pq[mb][hh * 2 + kk][0], pq[mb][hh * 2 + kk][1], pq[mb][hh * 2 + kk][2], pq[mb][hh * 2 + kk][3], db, 1);
        }
        wg_commit();
        wg_wait<0>();
        fence_regs(num);
#pragma unroll
        for (int h = 0; h < 2; h++) {
          float den = __shfl_sync(0xffffffffu, num[16 + 2 * h], lane & ~3);
          den = bfr(bfr(den) + 1e-6f);
          const float rden = 1.0f / den;
          const int r = wg * 128 + mb * 64 + w4 * 16 + g + h * 8;
#pragma unroll
          for (int j = 0; j < 4; j++) {
            const uint32_t n2 = pack2(num[4 * j + 2 * h], num[4 * j + 2 * h + 1]);
            const float o0 = lo_f(n2) * rden, o1 = hi_f(n2) * rden;
            const uint32_t off = r * 128 + (((hh * 4 + j) ^ (r & 7)) << 4) + t * 4;
            *reinterpret_cast<uint32_t*>(sgen + OFF_O + off) = pack2(o0, o1);
          }
        }
      }
    }
    named_bar_sync(1, 256);
    for (int i = tid; i < 256 * 8; i += 256) {
      const int r = i >> 3, c = i & 7;
      uint4 v = *reinterpret_cast<const uint4*>(sgen + OFF_O + r * 128 + ((c ^ (r & 7)) << 4));
      *reinterpret_cast<uint4*>(g_o + (size_t)(m0 + r) * DM + hp * 64 + c * 8) = v;
    }
    cluster_sync_all();
  }
}

namespace k3 {
constexpr int BM = 128, BN = 128, BK = 64, ST = 5;
constexpr int A_BYTES = BM * BK * 2, B_BYTES = BK * BN * 2, STAGE = A_BYTES + B_BYTES;
constexpr int OFF_BT = ST * STAGE;
constexpr int OFF_BAR = OFF_BT + 32768;
constexpr int SMEM = OFF_BAR + 1024 + 256;
}

__global__ void __cluster_dims__(2, 1, 1) __launch_bounds__(384, 1)
k3_out(const __grid_constant__ CUtensorMap tmo, const __grid_constant__ CUtensorMap tmw,
       const __grid_constant__ CUtensorMap tmbt, const __grid_constant__ CUtensorMap tmout) {
  using namespace k3;
  extern __shared__ uint8_t smem_raw[];
  const uint32_t sbase = (smem_u32(smem_raw) + 1023) & ~1023u;
  uint8_t* sgen = smem_raw + (sbase - smem_u32(smem_raw));
  const uint32_t bars = sbase + OFF_BAR;
  const uint32_t barbt = bars + 8 * 2 * ST;
  const int tid = threadIdx.x, warp = tid >> 5, lane = tid & 31;
  const uint32_t rank = cluster_ctarank();
  const int cl = blockIdx.x >> 1;
  const int mt = cl >> 2;
  const int nt = ((cl & 3) << 1) + rank;
  const int m0 = mt * BM, n0 = nt * BN;
  if (blockIdx.x == 0 && tid < 16) g_cnt[tid] = 0;

  if (tid == 0) {
    for (int s = 0; s < ST; s++) {
      mbar_init(bars + 8 * s, 1);
      mbar_init(bars + 8 * (ST + s), 16);
    }
    mbar_init(barbt, 1);
    asm volatile("fence.mbarrier_init.release.cluster;" ::: "memory");
  }
  cluster_sync_all();

  if (warp >= 8) {
    asm volatile("setmaxnreg.dec.sync.aligned.u32 40;");
    if (warp == 8 && lane == 0) {
      for (int kb = 0; kb < DM / BK; kb++) {
        const int s = kb % ST;
        mbar_wait(bars + 8 * (ST + s), ((kb / ST) & 1) ^ 1);
        const uint32_t full = bars + 8 * s;
        mbar_expect_tx(full, STAGE);
        const uint32_t sa = sbase + s * STAGE, sb = sa + A_BYTES;
        tma_load_2d_mc(sa + rank * 8192, &tmo, full, kb * BK, m0 + rank * 64, (uint16_t)3);
#pragma unroll
        for (int j = 0; j < 2; j++) tma_load_2d(sb + j * 8192, &tmw, full, n0 + j * 64, kb * BK);
        if (kb == 2) {
          mbar_expect_tx(barbt, 32768);
          tma_load_2d(sbase + OFF_BT, &tmbt, barbt, m0, n0);
          tma_load_2d(sbase + OFF_BT + 16384, &tmbt, barbt, m0 + 64, n0);
        }
      }
    }
    cluster_sync_all();
  } else {
    asm volatile("setmaxnreg.inc.sync.aligned.u32 232;");
    const int wg = warp >> 2, w4 = warp & 3, g = lane >> 2, t = lane & 3;
    float acc[64];
#pragma unroll
    for (int i = 0; i < 64; i++) acc[i] = 0.f;
    for (int kb = 0; kb < DM / BK; kb++) {
      const int s = kb % ST;
      mbar_wait(bars + 8 * s, (kb / ST) & 1);
      const uint32_t sa = sbase + s * STAGE + wg * 8192, sb = sbase + s * STAGE + A_BYTES;
      wg_fence();
#pragma unroll
      for (int ks = 0; ks < 4; ks++) {
        const uint64_t db = make_desc(sb + ks * 2048, 8192, 1024);
        const uint64_t da = make_desc(sa + ks * 32, 16, 1024);
        wgmma_ss_n128_tb(acc, da, db, 1);
      }
      wg_commit();
      if (kb > 0) {
        wg_wait<1>();
        const int sp = (kb - 1) % ST;
        if (lane == 0) { mbar_arrive_cluster(bars + 8 * (ST + sp), 0); mbar_arrive_cluster(bars + 8 * (ST + sp), 1); }
      }
    }
    wg_wait<0>();
    fence_regs(acc);
    named_bar_sync(1, 256);
    mbar_wait(barbt, 0);
#pragma unroll
    for (int h = 0; h < 2; h++) {
      const int rl = wg * 64 + w4 * 16 + g + h * 8;
      const float gt = g_gate[m0 + rl];
      const float omg = bfr(1.0f - gt);
      const uint8_t* bt = sgen + OFF_BT + wg * 16384;
      const int ll = rl & 63;
#pragma unroll
      for (int j = 0; j < 16; j++) {
        const int c = 8 * j + 2 * t;
        const float b0 = __bfloat162float(*reinterpret_cast<const bf16*>(bt + c * 128 + (((ll >> 3) ^ (c & 7)) << 4) + (ll & 7) * 2));
        const float b1 = __bfloat162float(*reinterpret_cast<const bf16*>(bt + (c + 1) * 128 + (((ll >> 3) ^ ((c + 1) & 7)) << 4) + (ll & 7) * 2));
        const uint32_t a2 = pack2(acc[4 * j + 2 * h], acc[4 * j + 2 * h + 1]);
        const float o0 = bfr(gt * lo_f(a2)) + bfr(omg * b0);
        const float o1 = bfr(gt * hi_f(a2)) + bfr(omg * b1);
        *reinterpret_cast<uint32_t*>(sgen + (j >> 3) * 16384 + rl * 128 + (((j & 7) ^ (rl & 7)) << 4) + t * 4) = pack2(o0, o1);
      }
    }
    fence_async_smem();
    named_bar_sync(2 + wg, 128);
    if ((tid & 127) == 0) {
#pragma unroll
      for (int j = 0; j < 2; j++)
        asm volatile("cp.async.bulk.tensor.2d.global.shared::cta.bulk_group [%0, {%2, %3}], [%1];" ::"l"(&tmout),
                     "r"(sbase + j * 16384 + wg * 8192), "r"(n0 + j * 64), "r"(m0 + wg * 64) : "memory");
      asm volatile("cp.async.bulk.commit_group;" ::: "memory");
      asm volatile("cp.async.bulk.wait_group.read 0;" ::: "memory");
    }
    cluster_sync_all();
  }
}

__device__ float g_kq[DM * 648];
constexpr int KOFF = 2048 + 16;
constexpr int KSZ = 2112;
constexpr int KCH = 2 * KSZ + 16;
__device__ __align__(1024) bf16 g_bT[DM * SEQ];

__device__ __forceinline__ void mma_bf16(float (&d)[4], uint32_t a0, uint32_t a1, uint32_t a2, uint32_t a3, uint32_t b0, uint32_t b1) {
  asm volatile("mma.sync.aligned.m16n8k16.row.col.f32.bf16.bf16.f32 {%0,%1,%2,%3}, {%4,%5,%6,%7}, {%8,%9}, {%0,%1,%2,%3};"
               : "+f"(d[0]), "+f"(d[1]), "+f"(d[2]), "+f"(d[3]) : "r"(a0), "r"(a1), "r"(a2), "r"(a3), "r"(b0), "r"(b1));
}
__device__ __forceinline__ void mma_tf32(float (&d)[4], uint32_t a0, uint32_t a1, uint32_t a2, uint32_t a3, uint32_t b0, uint32_t b1) {
  asm volatile("mma.sync.aligned.m16n8k8.row.col.f32.tf32.tf32.f32 {%0,%1,%2,%3}, {%4,%5,%6,%7}, {%8,%9}, {%0,%1,%2,%3};"
               : "+f"(d[0]), "+f"(d[1]), "+f"(d[2]), "+f"(d[3]) : "r"(a0), "r"(a1), "r"(a2), "r"(a3), "r"(b0), "r"(b1));
}
__device__ __forceinline__ uint32_t tf32r(float x) { uint32_t r; asm("cvt.rna.tf32.f32 %0, %1;" : "=r"(r) : "f"(x)); return r; }
struct cf { float r, i; };
__device__ __forceinline__ cf cmul(cf a, cf b) { cf c; c.r = a.r * b.r - a.i * b.i; c.i = a.r * b.i + a.i * b.r; return c; }
__device__ __forceinline__ cf csq(cf a) { cf c; c.r = a.r * a.r - a.i * a.i; c.i = 2.f * a.r * a.i; return c; }
__device__ __forceinline__ cf cexpp(float ar, float ai, float p) {
  const float e = ex2f(ar * p * 1.4426950408889634f);
  const float th = ai * p;
  const float k = rintf(th * 0.15915494309189535f);
  float r = fmaf(k, -6.2831854820251465f, th);
  r = fmaf(k, 1.7484556000744e-7f, r);
  cf w; w.r = e * __cosf(r); w.i = e * __sinf(r); return w;
}

__device__ __forceinline__ float shf(float v, int src) { return __shfl_sync(0xffffffffu, v, src); }
__device__ __forceinline__ void kgen_channel(int d, int lane, const bf16* __restrict__ logAr, const bf16* __restrict__ Aim,
                                             const bf16* __restrict__ Cre, const bf16* __restrict__ Cim,
                                             const bf16* __restrict__ logdt) {
  const int g = lane >> 2, t = lane & 3;
  const float dt = bfr(ex2f(__bfloat162float(logdt[d]) * 1.4426950408889634f));
  float acc[5][4];
#pragma unroll
  for (int a = 0; a < 5; a++)
#pragma unroll
    for (int b = 0; b < 4; b++) acc[a][b] = 0.f;
  float last = 0.f;
  const float fg = (float)g;
#pragma unroll 1
  for (int s = 0; s < 4; s++) {
    const int idx = d * NMODE + 32 * s + lane;
    const float m_ar = -bfr(ex2f(__bfloat162float(logAr[idx]) * 1.4426950408889634f)) * dt;
    const float m_ai = __bfloat162float(Aim[idx]) * dt;
    cf mC; mC.r = __bfloat162float(Cre[idx]) * dt; mC.i = __bfloat162float(Cim[idx]) * dt;
    const cf mW8 = cexpp(m_ar, m_ai, 8.f);
    const cf mW128 = cexpp(m_ar, m_ai, 128.f);
    const cf mW256 = csq(mW128), mW512 = csq(mW256), mW1024 = csq(mW512);
    const cf mW1536 = cmul(mW1024, mW512);
    {
      const cf w2048 = csq(mW1024);
      last += mC.r * w2048.r - mC.i * w2048.i;
    }
#pragma unroll 2
    for (int ks = 0; ks < 8; ks++) {
      const int src = 4 * ks + t;
      const float ar = shf(m_ar, src), ai = shf(m_ai, src);
      cf C, W8, W128, W256, W512, WA, WB;
      C.r = shf(mC.r, src); C.i = shf(mC.i, src);
      W8.r = shf(mW8.r, src); W8.i = shf(mW8.i, src);
      W128.r = shf(mW128.r, src); W128.i = shf(mW128.i, src);
      W256.r = shf(mW256.r, src); W256.i = shf(mW256.i, src);
      W512.r = shf(mW512.r, src); W512.i = shf(mW512.i, src);
      WA.r = shf(mW1024.r, src); WA.i = shf(mW1024.i, src);
      WB.r = shf(mW1536.r, src); WB.i = shf(mW1536.i, src);
      if (g >= 4) WA = WB;
      const cf E1 = cexpp(ar, ai, fg);
      const cf E16 = cexpp(ar, ai, 16.f * fg);
      const cf E8q = cexpp(ar, ai, 8.f * (float)(g & 3));
      const cf XAa = cmul(C, E16), XAb = cmul(XAa, W128);
      const cf E32 = csq(E16);
      const cf XBa = cmul(C, E32), XBb = cmul(XBa, W256);
      const cf Y2 = cmul(E1, W8);
      const cf E2 = csq(E1), E4 = csq(E2);
      const cf Y3 = cmul(E2, W256), Y4 = cmul(E4, W512), Y5 = cmul(E8q, WA);
      const uint32_t a0 = tf32r(XAa.r), a1 = tf32r(XAb.r), a2 = tf32r(-XAa.i), a3 = tf32r(-XAb.i);
      const uint32_t b0 = tf32r(XBa.r), b1 = tf32r(XBb.r), b2 = tf32r(-XBa.i), b3 = tf32r(-XBb.i);
      mma_tf32(acc[0], a0, a1, a2, a3, tf32r(E1.r), tf32r(E1.i));
      mma_tf32(acc[1], a0, a1, a2, a3, tf32r(Y2.r), tf32r(Y2.i));
      mma_tf32(acc[2], a0, a1, a2, a3, tf32r(Y3.r), tf32r(Y3.i));
      mma_tf32(acc[3], b0, b1, b2, b3, tf32r(Y4.r), tf32r(Y4.i));
      mma_tf32(acc[4], b0, b1, b2, b3, tf32r(Y5.r), tf32r(Y5.i));
    }
  }
  float* kq = g_kq + d * 648;
#pragma unroll
  for (int h = 0; h < 2; h++) {
    const int i = g + 8 * h;
    *reinterpret_cast<float2*>(kq + 16 * i + 2 * t) = make_float2(2.f * acc[0][2 * h], 2.f * acc[0][2 * h + 1]);
    *reinterpret_cast<float2*>(kq + 16 * i + 8 + 2 * t) = make_float2(2.f * acc[1][2 * h], 2.f * acc[1][2 * h + 1]);
    *reinterpret_cast<float2*>(kq + 256 + 8 * i + 2 * t) = make_float2(2.f * acc[2][2 * h], 2.f * acc[2][2 * h + 1]);
    *reinterpret_cast<float2*>(kq + 384 + 8 * i + 2 * t) = make_float2(2.f * acc[3][2 * h], 2.f * acc[3][2 * h + 1]);
    *reinterpret_cast<float2*>(kq + 512 + 4 * i + 64 * (t >> 1) + 2 * (t & 1)) = make_float2(2.f * acc[4][2 * h], 2.f * acc[4][2 * h + 1]);
  }
#pragma unroll
  for (int o = 16; o; o >>= 1) last += __shfl_xor_sync(0xffffffffu, last, o);
  if (lane == 0) kq[640] = 2.f * last;
}

__global__ void __launch_bounds__(256)
k0_kgen(const bf16* __restrict__ x, const bf16* __restrict__ logAr, const bf16* __restrict__ Aim, const bf16* __restrict__ Cre,
        const bf16* __restrict__ Cim, const bf16* __restrict__ logdt, const bf16* __restrict__ gatew) {
  const int warp = threadIdx.x >> 5, lane = threadIdx.x & 31;
  for (int rr = 0; rr < 2; rr++) {
    const int r = blockIdx.x * 16 + warp * 2 + rr;
    float s = 0.f;
    for (int c = lane * 8; c < DM; c += 256) {
      uint4 xv = *reinterpret_cast<const uint4*>(x + (size_t)r * DM + c);
      uint4 wv = *reinterpret_cast<const uint4*>(gatew + c);
      const bf16* xp = reinterpret_cast<const bf16*>(&xv);
      const bf16* wp = reinterpret_cast<const bf16*>(&wv);
#pragma unroll
      for (int q = 0; q < 8; q++) s += bfr(__bfloat162float(xp[q]) * __bfloat162float(wp[q]));
    }
#pragma unroll
    for (int o = 16; o; o >>= 1) s += __shfl_xor_sync(0xffffffffu, s, o);
    if (lane == 0) { float z = bfr(s); g_gate[r] = bfr(1.0f / (1.0f + expf(-z))); }
  }
  kgen_channel(blockIdx.x * 8 + warp, lane, logAr, Aim, Cre, Cim, logdt);
}

namespace k2 {
constexpr int CH = 8;
constexpr int UPAD = 128;
constexpr int USZ = UPAD + SEQ;
constexpr int OFF_U = 0;
constexpr int OFF_K = OFF_U + CH * USZ * 2;
constexpr int OFF_R = OFF_K + CH * KCH * 2;
constexpr int SMEM = OFF_R + CH * SEQ * 4;
}

__global__ void __launch_bounds__(512, 1)
k2_conv(const bf16* __restrict__ x, const bf16* __restrict__ Dskip) {
  using namespace k2;
  extern __shared__ __align__(16) uint8_t sm[];
  const int tid = threadIdx.x, warp = tid >> 5, lane = tid & 31, g = lane >> 2, t = lane & 3;
  const int ch = warp >> 1, half = warp & 1;
  const int d0 = blockIdx.x * CH;
  bf16* us = reinterpret_cast<bf16*>(sm + OFF_U);
  bf16* ks = reinterpret_cast<bf16*>(sm + OFF_K);
  float* kqs = reinterpret_cast<float*>(sm + OFF_R) + ch * SEQ;
  {
    const float* kq = g_kq + (d0 + ch) * 648;
#pragma unroll
    for (int i = 0; i < 11; i++) {
      const int o = (i * 2 + half) * 32 + lane;
      if (o < 648) kqs[o] = __ldcg(kq + o);
    }
  }
  if (tid < CH * UPAD / 2) {
    const int c = tid / (UPAD / 2), o = tid % (UPAD / 2);
    reinterpret_cast<uint32_t*>(us + c * USZ)[o] = 0u;
  }
  {
    uint4 v[2][2];
#pragma unroll
    for (int it = 0; it < 2; it++) {
      const int l = 2 * (tid + it * 512);
      v[it][0] = __ldg(reinterpret_cast<const uint4*>(x + (size_t)l * DM + d0));
      v[it][1] = __ldg(reinterpret_cast<const uint4*>(x + (size_t)(l + 1) * DM + d0));
    }
#pragma unroll
    for (int it = 0; it < 2; it++) {
      const int l = 2 * (tid + it * 512);
      const int e = l & 15;
      const int pe = ((e & 7) >> 1) * 4 + (e >> 3) * 2;
      const int pos = UPAD + (l & ~15) + pe;
      const uint32_t a[4] = {v[it][0].x, v[it][0].y, v[it][0].z, v[it][0].w};
      const uint32_t b[4] = {v[it][1].x, v[it][1].y, v[it][1].z, v[it][1].w};
#pragma unroll
      for (int c = 0; c < 4; c++) {
        *reinterpret_cast<uint32_t*>(us + (2 * c) * USZ + pos) = __byte_perm(a[c], b[c], 0x5410);
        *reinterpret_cast<uint32_t*>(us + (2 * c + 1) * USZ + pos) = __byte_perm(a[c], b[c], 0x7632);
      }
    }
  }
  named_bar_sync(1 + ch, 64);
  {
    uint32_t* kr = reinterpret_cast<uint32_t*>(ks + ch * KCH);
    uint32_t* kr2 = reinterpret_cast<uint32_t*>(ks + ch * KCH + KSZ + 16);
#pragma unroll 3
    for (int w = half * 528 + lane; w < (half + 1) * 528; w += 32) {
      float kv[3];
#pragma unroll
      for (int q = 0; q < 3; q++) {
        const int xk = KOFF - 2 * w - q;
        float val = 0.f;
        if (xk >= 0 && xk < SEQ) {
          const uint32_t pb = __float_as_uint(bfr((float)xk));
          const int id = xk < 256 ? xk : (256 + ((int)(pb >> 23) - 135) * 128 + (int)((pb >> 16) & 127));
          val = kqs[id];
        }
        kv[q] = val;
      }
      kr[w] = pack2(kv[0], kv[1]);
      kr2[w] = pack2(kv[1], kv[2]);
    }
  }
  __syncthreads();

  float D[16][4];
#pragma unroll
  for (int j = 0; j < 16; j++)
#pragma unroll
    for (int q = 0; q < 4; q++) D[j][q] = 0.f;
  const bf16* uc = us + ch * USZ + UPAD;
  {
    const bf16* kr = ks + ch * KCH;
    const uint32_t* fbase = reinterpret_cast<const uint32_t*>((g & 1) ? (kr + KSZ + 16) : kr) + ((KOFF - g + 2 * t) >> 1);
    for (int r = half * 4; r < half * 4 + 4; r++) {
      uint32_t B[16][2];
#pragma unroll
      for (int j = 0; j < 16; j++) {
        const uint2 v = *reinterpret_cast<const uint2*>(uc + 16 * (8 * j - r + g) + 4 * t);
        B[j][0] = v.x; B[j][1] = v.y;
      }
      uint32_t fm1 = fbase[-4 * (2 * r - 1)];
#pragma unroll
      for (int k = 0; k < 16; k++) {
        const int dl = 8 * k + r;
        const uint32_t f0 = fbase[-4 * (2 * dl)];
        const uint32_t f1 = fbase[-4 * (2 * dl + 1)];
        if (k > 0) fm1 = fbase[-4 * (2 * dl - 1)];
#pragma unroll
        for (int j = k; j < 16; j++) mma_bf16(D[j], f0, f1, fm1, f0, B[j - k][0], B[j - k][1]);
      }
    }
  }
  float* red = reinterpret_cast<float*>(sm + OFF_R) + ch * SEQ;
#pragma unroll
  for (int j = 0; j < 8; j++) {
    const int jo = half ? j : j + 8;
    *reinterpret_cast<float4*>(red + (jo * 32 + lane) * 4) =
        make_float4(half ? D[j][0] : D[j + 8][0], half ? D[j][1] : D[j + 8][1], half ? D[j][2] : D[j + 8][2], half ? D[j][3] : D[j + 8][3]);
  }
  named_bar_sync(1 + ch, 64);
  {
    const float dsk = __bfloat162float(Dskip[d0 + ch]);
    uint32_t outp[8][2];
#pragma unroll
    for (int j = 0; j < 8; j++) {
      const int jm = half ? j + 8 : j;
      const float4 o = *reinterpret_cast<const float4*>(red + (jm * 32 + lane) * 4);
      const float dd[4] = {(half ? D[j + 8][0] : D[j][0]) + o.x, (half ? D[j + 8][1] : D[j][1]) + o.y,
                           (half ? D[j + 8][2] : D[j][2]) + o.z, (half ? D[j + 8][3] : D[j][3]) + o.w};
      float y[4];
#pragma unroll
      for (int q = 0; q < 4; q++) {
        const int a = 8 * jm + 2 * t + (q & 1), bb = g + (q >> 1) * 8;
        const int pe = ((bb & 7) >> 1) * 4 + (bb >> 3) * 2 + (bb & 1);
        const float uv = __bfloat162float(uc[16 * a + pe]);
        y[q] = bfr(dd[q]) + bfr(uv * dsk);
      }
      outp[j][0] = pack2(y[0], y[1]);
      outp[j][1] = pack2(y[2], y[3]);
    }
    named_bar_sync(1 + ch, 64);
    bf16* ys = reinterpret_cast<bf16*>(red);
#pragma unroll
    for (int j = 0; j < 8; j++) {
      const int jm = half ? j + 8 : j;
      const int a = 8 * jm + 2 * t;
      const uint32_t p0 = outp[j][0], p1 = outp[j][1];
      reinterpret_cast<uint16_t*>(ys)[16 * a + g] = (uint16_t)(p0 & 0xffff);
      reinterpret_cast<uint16_t*>(ys)[16 * (a + 1) + g] = (uint16_t)(p0 >> 16);
      reinterpret_cast<uint16_t*>(ys)[16 * a + g + 8] = (uint16_t)(p1 & 0xffff);
      reinterpret_cast<uint16_t*>(ys)[16 * (a + 1) + g + 8] = (uint16_t)(p1 >> 16);
    }
    __syncwarp();
    bf16* dst = g_bT + (size_t)(d0 + ch) * SEQ + half * 1024;
#pragma unroll
    for (int i = 0; i < 4; i++) {
      const uint4 v = *reinterpret_cast<const uint4*>(ys + half * 1024 + (i * 32 + lane) * 8);
      *reinterpret_cast<uint4*>(dst + (i * 32 + lane) * 8) = v;
    }
  }
}

typedef CUresult (*EncodeFn)(CUtensorMap*, CUtensorMapDataType, cuuint32_t, void*, const cuuint64_t*, const cuuint64_t*,
                             const cuuint32_t*, const cuuint32_t*, CUtensorMapInterleave, CUtensorMapSwizzle,
                             CUtensorMapL2promotion, CUtensorMapFloatOOBfill);

static void make_map(EncodeFn enc, CUtensorMap* m, void* ptr, uint64_t inner, uint64_t outer, uint32_t bi, uint32_t bo) {
  cuuint64_t dims[2] = {inner, outer};
  cuuint64_t strides[1] = {inner * 2};
  cuuint32_t box[2] = {bi, bo};
  cuuint32_t es[2] = {1, 1};
  enc(m, CU_TENSOR_MAP_DATA_TYPE_BFLOAT16, 2, ptr, dims, strides, box, es, CU_TENSOR_MAP_INTERLEAVE_NONE,
      CU_TENSOR_MAP_SWIZZLE_128B, CU_TENSOR_MAP_L2_PROMOTION_L2_256B, CU_TENSOR_MAP_FLOAT_OOB_FILL_NONE);
}

extern "C" void kernel_launch(void* const* d_in, const int* in_sizes, int n_in, void* d_out, int out_size) {
  const bf16* x = (const bf16*)d_in[0];
  const bf16* wqkv = (const bf16*)d_in[1];
  const bf16* wo = (const bf16*)d_in[2];
  const bf16* logAr = (const bf16*)d_in[4];
  const bf16* Aim = (const bf16*)d_in[5];
  const bf16* Cre = (const bf16*)d_in[6];
  const bf16* Cim = (const bf16*)d_in[7];
  const bf16* logdt = (const bf16*)d_in[8];
  const bf16* Dskip = (const bf16*)d_in[9];
  const bf16* gatew = (const bf16*)d_in[10];

  static EncodeFn enc = nullptr;
  static void* p_o = nullptr;
  static void* p_bT = nullptr;
  if (!enc) {
    void* fn = nullptr;
    cudaDriverEntryPointQueryResult qr;
    cudaGetDriverEntryPoint("cuTensorMapEncodeTiled", &fn, cudaEnableDefault, &qr);
    enc = (EncodeFn)fn;
    cudaGetSymbolAddress(&p_o, g_o);
    cudaGetSymbolAddress(&p_bT, g_bT);
    cudaFuncSetAttribute(k1_qkv_attn, cudaFuncAttributeMaxDynamicSharedMemorySize, k1::SMEM);
    cudaFuncSetAttribute(k2_conv, cudaFuncAttributeMaxDynamicSharedMemorySize, k2::SMEM);
    cudaFuncSetAttribute(k3_out, cudaFuncAttributeMaxDynamicSharedMemorySize, k3::SMEM);
  }
  CUtensorMap tmx, tmw, tmo, tmwo, tmbt, tmout;
  make_map(enc, &tmx, (void*)x, 1024, 2048, 64, 128);
  make_map(enc, &tmw, (void*)wqkv, 3072, 1024, 64, 64);
  make_map(enc, &tmo, p_o, 1024, 2048, 64, 64);
  make_map(enc, &tmwo, (void*)wo, 1024, 1024, 64, 64);
  make_map(enc, &tmbt, p_bT, 2048, 1024, 64, 128);
  make_map(enc, &tmout, d_out, 1024, 2048, 64, 64);

  k0_kgen<<<128, 256>>>(x, logAr, Aim, Cre, Cim, logdt, gatew);
  k2_conv<<<128, 512, k2::SMEM>>>(x, Dskip);
  k1_qkv_attn<<<128, 384, k1::SMEM>>>(tmx, tmw);
  k3_out<<<128, 384, k3::SMEM>>>(tmo, tmwo, tmbt, tmout);
}
```

```cpp
#include <cuda_runtime.h>
#include <cuda_bf16.h>
#include <cuda.h>
#include <stdint.h>

typedef __nv_bfloat16 bf16;

constexpr int SEQ = 2048, DM = 1024, NMODE = 128;

__device__ __align__(1024) bf16 g_o[SEQ * DM];
__device__ __align__(1024) bf16 g_b[SEQ * DM];
__device__ float g_gate[SEQ];
__device__ __align__(16) float g_part[16 * 8 * 2 * 1056];
__device__ unsigned int g_cnt[16];

#define TS(k, i) do {} while (0)
__device__ __forceinline__ uint32_t smem_u32(const void* p) { return (uint32_t)__cvta_generic_to_shared(p); }
__device__ __forceinline__ void mbar_init(uint32_t bar, uint32_t cnt) {
  asm volatile("mbarrier.init.shared::cta.b64 [%0], %1;" ::"r"(bar), "r"(cnt));
}
__device__ __forceinline__ void mbar_expect_tx(uint32_t bar, uint32_t bytes) {
  asm volatile("mbarrier.arrive.expect_tx.shared::cta.b64 _, [%0], %1;" ::"r"(bar), "r"(bytes) : "memory");
}
__device__ __forceinline__ void mbar_arrive_cluster(uint32_t bar, uint32_t cta) {
  asm volatile(
      "{\n.reg .b32 ra;\nmapa.shared::cluster.u32 ra, %0, %1;\n"
      "mbarrier.arrive.shared::cluster.b64 _, [ra];\n}\n" ::"r"(bar), "r"(cta) : "memory");
}
__device__ __forceinline__ bool mbar_try_wait(uint32_t bar, uint32_t parity) {
  uint32_t ok;
  asm volatile(
      "{\n.reg .pred p;\nmbarrier.try_wait.parity.shared::cta.b64 p, [%1], %2;\nselp.u32 %0, 1, 0, p;\n}\n"
      : "=r"(ok) : "r"(bar), "r"(parity) : "memory");
  return ok;
}
__device__ __forceinline__ void mbar_wait(uint32_t bar, uint32_t parity) {
  while (!mbar_try_wait(bar, parity)) {}
}
__device__ __forceinline__ void tma_load_2d(uint32_t dst, const CUtensorMap* map, uint32_t bar, int c0, int c1) {
  asm volatile(
      "cp.async.bulk.tensor.2d.shared::cluster.global.mbarrier::complete_tx::bytes [%0], [%1, {%3, %4}], [%2];" ::"r"(dst),
      "l"(map), "r"(bar), "r"(c0), "r"(c1) : "memory");
}
__device__ __forceinline__ void tma_load_2d_mc(uint32_t dst, const CUtensorMap* map, uint32_t bar, int c0, int c1,
                                               uint16_t mask) {
  asm volatile(
      "cp.async.bulk.tensor.2d.shared::cluster.global.mbarrier::complete_tx::bytes.multicast::cluster [%0], [%1, {%3, %4}], [%2], %5;" ::"r"(dst),
      "l"(map), "r"(bar), "r"(c0), "r"(c1), "h"(mask) : "memory");
}
__device__ __forceinline__ void cluster_sync_all() {
  asm volatile("barrier.cluster.arrive.release.aligned;\nbarrier.cluster.wait.acquire.aligned;\n" ::: "memory");
}
__device__ __forceinline__ uint32_t cluster_ctarank() {
  uint32_t r; asm volatile("mov.u32 %0, %%cluster_ctarank;" : "=r"(r)); return r;
}
__device__ __forceinline__ void named_bar_sync(int id, int n) { asm volatile("bar.sync %0, %1;" ::"r"(id), "r"(n) : "memory"); }
__device__ __forceinline__ void fence_async_smem() { asm volatile("fence.proxy.async.shared::cta;" ::: "memory"); }
__device__ __forceinline__ void wg_fence() { asm volatile("wgmma.fence.sync.aligned;" ::: "memory"); }
__device__ __forceinline__ void wg_commit() { asm volatile("wgmma.commit_group.sync.aligned;" ::: "memory"); }
template <int N> __device__ __forceinline__ void wg_wait() { asm volatile("wgmma.wait_group.sync.aligned %0;" ::"n"(N) : "memory"); }
__device__ __forceinline__ uint64_t make_desc(uint32_t addr, uint32_t lbo, uint32_t sbo) {
  return (uint64_t)((addr & 0x3FFFF) >> 4) | ((uint64_t)(lbo >> 4) << 16) | ((uint64_t)(sbo >> 4) << 32) | (1ull << 62);
}
__device__ __forceinline__ float bfr(float x) { return __bfloat162float(__float2bfloat16_rn(x)); }
__device__ __forceinline__ uint32_t pack2(float lo, float hi) {
  __nv_bfloat162 v = __floats2bfloat162_rn(lo, hi);
  return *reinterpret_cast<uint32_t*>(&v);
}
__device__ __forceinline__ float ex2f(float x) { float r; asm("ex2.approx.ftz.f32 %0, %1;" : "=f"(r) : "f"(x)); return r; }
__device__ __forceinline__ float lo_f(uint32_t v) { return __uint_as_float(v << 16); }
__device__ __forceinline__ float hi_f(uint32_t v) { return __uint_as_float(v & 0xffff0000u); }
__device__ __forceinline__ uint32_t phi2(float a0, float a1) {
  const uint32_t t2 = pack2(a0, a1);
  const float t0 = lo_f(t2), t1 = hi_f(t2);
  const float e0 = ex2f(t0 * 1.4426950408889634f), e1 = ex2f(t1 * 1.4426950408889634f);
  const float f0 = t0 > 0.f ? t0 + 1.0f : e0;
  const float f1 = t1 > 0.f ? t1 + 1.0f : e1;
  const uint32_t f2 = pack2(f0, f1);
  return pack2(lo_f(f2) + 1e-6f, hi_f(f2) + 1e-6f);
}
template <int R> __device__ __forceinline__ void fence_regs(float (&d)[R]) {
#pragma unroll
  for (int i = 0; i < R; i++) asm volatile("" : "+f"(d[i])::"memory");
}

__device__ __forceinline__ void wgmma_ss_n192_tb(float (&d)[96], uint64_t da, uint64_t db, int sc) {
  asm volatile("{\n.reg .pred p;\nsetp.ne.b32 p, %98, 0;\n"
    "wgmma.mma_async.sync.aligned.m64n192k16.f32.bf16.bf16 {%0, %1, %2, %3, %4, %5, %6, %7, %8, %9, %10, %11, %12, %13, %14, %15, %16, %17, %18, %19, %20, %21, %22, %23, %24, %25, %26, %27, %28, %29, %30, %31, %32, %33, %34, %35, %36, %37, %38, %39, %40, %41, %42, %43, %44, %45, %46, %47, %48, %49, %50, %51, %52, %53, %54, %55, %56, %57, %58, %59, %60, %61, %62, %63, %64, %65, %66, %67, %68, %69, %70, %71, %72, %73, %74, %75, %76, %77, %78, %79, %80, %81, %82, %83, %84, %85, %86, %87, %88, %89, %90, %91, %92, %93, %94, %95}, %96, %97, p, 1, 1, 0, 1;\n}\n"
    : "+f"(d[0]), "+f"(d[1]), "+f"(d[2]), "+f"(d[3]), "+f"(d[4]), "+f"(d[5]), "+f"(d[6]), "+f"(d[7]), "+f"(d[8]), "+f"(d[9]), "+f"(d[10]), "+f"(d[11]), "+f"(d[12]), "+f"(d[13]), "+f"(d[14]), "+f"(d[15]), "+f"(d[16]), "+f"(d[17]), "+f"(d[18]), "+f"(d[19]), "+f"(d[20]), "+f"(d[21]), "+f"(d[22]), "+f"(d[23]), "+f"(d[24]), "+f"(d[25]), "+f"(d[26]), "+f"(d[27]), "+f"(d[28]), "+f"(d[29]), "+f"(d[30]), "+f"(d[31]), "+f"(d[32]), "+f"(d[33]), "+f"(d[34]), "+f"(d[35]), "+f"(d[36]), "+f"(d[37]), "+f"(d[38]), "+f"(d[39]), "+f"(d[40]), "+f"(d[41]), "+f"(d[42]), "+f"(d[43]), "+f"(d[44]), "+f"(d[45]), "+f"(d[46]), "+f"(d[47]), "+f"(d[48]), "+f"(d[49]), "+f"(d[50]), "+f"(d[51]), "+f"(d[52]), "+f"(d[53]), "+f"(d[54]), "+f"(d[55]), "+f"(d[56]), "+f"(d[57]), "+f"(d[58]), "+f"(d[59]), "+f"(d[60]), "+f"(d[61]), "+f"(d[62]), "+f"(d[63]), "+f"(d[64]), "+f"(d[65]), "+f"(d[66]), "+f"(d[67]), "+f"(d[68]), "+f"(d[69]), "+f"(d[70]), "+f"(d[71]), "+f"(d[72]), "+f"(d[73]), "+f"(d[74]), "+f"(d[75]), "+f"(d[76]), "+f"(d[77]), "+f"(d[78]), "+f"(d[79]), "+f"(d[80]), "+f"(d[81]), "+f"(d[82]), "+f"(d[83]), "+f"(d[84]), "+f"(d[85]), "+f"(d[86]), "+f"(d[87]), "+f"(d[88]), "+f"(d[89]), "+f"(d[90]), "+f"(d[91]), "+f"(d[92]), "+f"(d[93]), "+f"(d[94]), "+f"(d[95])
    : "l"(da), "l"(db), "r"(sc));
}

__device__ __forceinline__ void wgmma_ss_n128_tb(float (&d)[64], uint64_t da, uint64_t db, int sc) {
  asm volatile("{\n.reg .pred p;\nsetp.ne.b32 p, %66, 0;\n"
    "wgmma.mma_async.sync.aligned.m64n128k16.f32.bf16.bf16 {%0, %1, %2, %3, %4, %5, %6, %7, %8, %9, %10, %11, %12, %13, %14, %15, %16, %17, %18, %19, %20, %21, %22, %23, %24, %25, %26, %27, %28, %29, %30, %31, %32, %33, %34, %35, %36, %37, %38, %39, %40, %41, %42, %43, %44, %45, %46, %47, %48, %49, %50, %51, %52, %53, %54, %55, %56, %57, %58, %59, %60, %61, %62, %63}, %64, %65, p, 1, 1, 0, 1;\n}\n"
    : "+f"(d[0]), "+f"(d[1]), "+f"(d[2]), "+f"(d[3]), "+f"(d[4]), "+f"(d[5]), "+f"(d[6]), "+f"(d[7]), "+f"(d[8]), "+f"(d[9]), "+f"(d[10]), "+f"(d[11]), "+f"(d[12]), "+f"(d[13]), "+f"(d[14]), "+f"(d[15]), "+f"(d[16]), "+f"(d[17]), "+f"(d[18]), "+f"(d[19]), "+f"(d[20]), "+f"(d[21]), "+f"(d[22]), "+f"(d[23]), "+f"(d[24]), "+f"(d[25]), "+f"(d[26]), "+f"(d[27]), "+f"(d[28]), "+f"(d[29]), "+f"(d[30]), "+f"(d[31]), "+f"(d[32]), "+f"(d[33]), "+f"(d[34]), "+f"(d[35]), "+f"(d[36]), "+f"(d[37]), "+f"(d[38]), "+f"(d[39]), "+f"(d[40]), "+f"(d[41]), "+f"(d[42]), "+f"(d[43]), "+f"(d[44]), "+f"(d[45]), "+f"(d[46]), "+f"(d[47]), "+f"(d[48]), "+f"(d[49]), "+f"(d[50]), "+f"(d[51]), "+f"(d[52]), "+f"(d[53]), "+f"(d[54]), "+f"(d[55]), "+f"(d[56]), "+f"(d[57]), "+f"(d[58]), "+f"(d[59]), "+f"(d[60]), "+f"(d[61]), "+f"(d[62]), "+f"(d[63])
    : "l"(da), "l"(db), "r"(sc));
}

__device__ __forceinline__ void wgmma_ss_n64_tatb(float (&d)[32], uint64_t da, uint64_t db, int sc) {
  asm volatile("{\n.reg .pred p;\nsetp.ne.b32 p, %34, 0;\n"
    "wgmma.mma_async.sync.aligned.m64n64k16.f32.bf16.bf16 {%0, %1, %2, %3, %4, %5, %6, %7, %8, %9, %10, %11, %12, %13, %14, %15, %16, %17, %18, %19, %20, %21, %22, %23, %24, %25, %26, %27, %28, %29, %30, %31}, %32, %33, p, 1, 1, 1, 1;\n}\n"
    : "+f"(d[0]), "+f"(d[1]), "+f"(d[2]), "+f"(d[3]), "+f"(d[4]), "+f"(d[5]), "+f"(d[6]), "+f"(d[7]), "+f"(d[8]), "+f"(d[9]), "+f"(d[10]), "+f"(d[11]), "+f"(d[12]), "+f"(d[13]), "+f"(d[14]), "+f"(d[15]), "+f"(d[16]), "+f"(d[17]), "+f"(d[18]), "+f"(d[19]), "+f"(d[20]), "+f"(d[21]), "+f"(d[22]), "+f"(d[23]), "+f"(d[24]), "+f"(d[25]), "+f"(d[26]), "+f"(d[27]), "+f"(d[28]), "+f"(d[29]), "+f"(d[30]), "+f"(d[31])
    : "l"(da), "l"(db), "r"(sc));
}

__device__ __forceinline__ void wgmma_ss_n8_tatb(float (&d)[4], uint64_t da, uint64_t db, int sc) {
  asm volatile("{\n.reg .pred p;\nsetp.ne.b32 p, %6, 0;\n"
    "wgmma.mma_async.sync.aligned.m64n8k16.f32.bf16.bf16 {%0, %1, %2, %3}, %4, %5, p, 1, 1, 1, 1;\n}\n"
    : "+f"(d[0]), "+f"(d[1]), "+f"(d[2]), "+f"(d[3])
    : "l"(da), "l"(db), "r"(sc));
}

__device__ __forceinline__ void wgmma_rs_n40_tb(float (&d)[20], uint32_t a0, uint32_t a1, uint32_t a2, uint32_t a3, uint64_t db, int sc) {
  asm volatile("{\n.reg .pred p;\nsetp.ne.b32 p, %25, 0;\n"
    "wgmma.mma_async.sync.aligned.m64n40k16.f32.bf16.bf16 {%0, %1, %2, %3, %4, %5, %6, %7, %8, %9, %10, %11, %12, %13, %14, %15, %16, %17, %18, %19}, {%20, %21, %22, %23}, %24, p, 1, 1, 1;\n}\n"
    : "+f"(d[0]), "+f"(d[1]), "+f"(d[2]), "+f"(d[3]), "+f"(d[4]), "+f"(d[5]), "+f"(d[6]), "+f"(d[7]), "+f"(d[8]), "+f"(d[9]), "+f"(d[10]), "+f"(d[11]), "+f"(d[12]), "+f"(d[13]), "+f"(d[14]), "+f"(d[15]), "+f"(d[16]), "+f"(d[17]), "+f"(d[18]), "+f"(d[19])
    : "r"(a0), "r"(a1), "r"(a2), "r"(a3), "l"(db), "r"(sc));
}

namespace k1 {
constexpr int BM = 256, BN = 192, BK = 64, ST = 4;
constexpr int A_BYTES = BM * BK * 2, B_BYTES = BK * BN * 2, STAGE = A_BYTES + B_BYTES;
constexpr int SMEM = ST * STAGE + 1024 + 256;
constexpr int OFF_PK = 0, OFF_V = 32768, OFF_ONES = 65536, OFF_KV = 69632, OFF_O = 81920, OFF_RED = 114688;
}

__global__ void __cluster_dims__(2, 1, 1) __launch_bounds__(384, 1)
k1_qkv_attn(const __grid_constant__ CUtensorMap tmx, const __grid_constant__ CUtensorMap tmw) {
  using namespace k1;
  extern __shared__ uint8_t smem_raw[];
  const uint32_t sbase = (smem_u32(smem_raw) + 1023) & ~1023u;
  uint8_t* sgen = smem_raw + (sbase - smem_u32(smem_raw));
  const uint32_t bars = sbase + ST * STAGE;
  const int tid = threadIdx.x, warp = tid >> 5, lane = tid & 31;
  const uint32_t rank = cluster_ctarank();
  const int cl = blockIdx.x >> 1;
  const int mt = cl >> 3;
  const int hp = ((cl & 7) << 1) + rank;
  const int m0 = mt * BM;

  if (tid == 0) {
    for (int s = 0; s < ST; s++) {
      mbar_init(bars + 8 * s, 1);
      mbar_init(bars + 8 * (ST + s), 16);
    }
    asm volatile("fence.mbarrier_init.release.cluster;" ::: "memory");
  }
  cluster_sync_all();

  if (warp >= 8) {
    asm volatile("setmaxnreg.dec.sync.aligned.u32 40;");
    if (warp == 8 && lane == 0) {
      for (int kb = 0; kb < DM / BK; kb++) {
        const int s = kb % ST;
        mbar_wait(bars + 8 * (ST + s), ((kb / ST) & 1) ^ 1);
        const uint32_t full = bars + 8 * s;
        mbar_expect_tx(full, STAGE);
        const uint32_t sa = sbase + s * STAGE, sb = sa + A_BYTES;
        tma_load_2d_mc(sa + rank * 16384, &tmx, full, kb * BK, m0 + rank * 128, (uint16_t)3);
#pragma unroll
        for (int j = 0; j < 3; j++) tma_load_2d(sb + j * 8192, &tmw, full, j * 1024 + hp * 64, kb * BK);
      }
    }
    cluster_sync_all();
  } else {
    asm volatile("setmaxnreg.inc.sync.aligned.u32 232;");
    const int wg = warp >> 2, w4 = warp & 3, g = lane >> 2, t = lane & 3;
    if (tid == 0) TS(1, 0);
    float acc[2][96];
#pragma unroll
    for (int i = 0; i < 96; i++) { acc[0][i] = 0.f; acc[1][i] = 0.f; }
    for (int kb = 0; kb < DM / BK; kb++) {
      const int s = kb % ST;
      mbar_wait(bars + 8 * s, (kb / ST) & 1);
      const uint32_t sa = sbase + s * STAGE + wg * 16384, sb = sbase + s * STAGE + A_BYTES;
      wg_fence();
#pragma unroll
      for (int ks = 0; ks < 4; ks++) {
        const uint64_t db = make_desc(sb + ks * 2048, 8192, 1024);
#pragma unroll
        for (int mb = 0; mb < 2; mb++) {
          const uint64_t da = make_desc(sa + mb * 8192 + ks * 32, 16, 1024);
          wgmma_ss_n192_tb(acc[mb], da, db, 1);
        }
      }
      wg_commit();
      if (kb > 0) {
        wg_wait<1>();
        const int sp = (kb - 1) % ST;
        if (lane == 0) { mbar_arrive_cluster(bars + 8 * (ST + sp), 0); mbar_arrive_cluster(bars + 8 * (ST + sp), 1); }
      }
    }
    wg_wait<0>();
    fence_regs(acc[0]); fence_regs(acc[1]);
    if (tid == 0) TS(1, 1);
    named_bar_sync(1, 256);

#pragma unroll
    for (int mb = 0; mb < 2; mb++) {
#pragma unroll
      for (int h = 0; h < 2; h++) {
        const int r = wg * 128 + mb * 64 + w4 * 16 + g + h * 8;
#pragma unroll
        for (int j = 0; j < 8; j++) {
          const uint32_t off = r * 128 + ((j ^ (r & 7)) << 4) + t * 4;
          const float k0 = acc[mb][4 * (8 + j) + 2 * h], k1v = acc[mb][4 * (8 + j) + 2 * h + 1];
          const float v0 = acc[mb][4 * (16 + j) + 2 * h], v1 = acc[mb][4 * (16 + j) + 2 * h + 1];
          *reinterpret_cast<uint32_t*>(sgen + OFF_PK + off) = phi2(k0, k1v);
          *reinterpret_cast<uint32_t*>(sgen + OFF_V + off) = pack2(v0, v1);
        }
      }
    }
    if (tid < 256) *reinterpret_cast<uint32_t*>(sgen + OFF_ONES + tid * 4) = 0x3F803F80u;
    fence_async_smem();
    named_bar_sync(1, 256);

    if (tid == 0) TS(1, 2);
    float* part = g_part + (size_t)(hp * 8 + mt) * 2112;
    {
      float kv[32], zz[4];
#pragma unroll
      for (int i = 0; i < 32; i++) kv[i] = 0.f;
#pragma unroll
      for (int i = 0; i < 4; i++) zz[i] = 0.f;
      wg_fence();
#pragma unroll
      for (int ks = 0; ks < 8; ks++) {
        const uint64_t da = make_desc(sbase + OFF_PK + wg * 16384 + ks * 2048, 16, 1024);
        const uint64_t db = make_desc(sbase + OFF_V + wg * 16384 + ks * 2048, 16, 1024);
        const uint64_t d1 = make_desc(sbase + OFF_ONES, 16, 0);
        wgmma_ss_n64_tatb(kv, da, db, 1);
        wgmma_ss_n8_tatb(zz, da, d1, 1);
      }
      wg_commit();
      wg_wait<0>();
      fence_regs(kv); fence_regs(zz);
      const int hh = w4 >> 1;
      float* red = reinterpret_cast<float*>(sgen + OFF_RED);
      float vals[2][4][2];
#pragma unroll
      for (int h = 0; h < 2; h++)
#pragma unroll
        for (int j = 0; j < 4; j++) {
          vals[h][j][0] = hh ? kv[4 * (4 + j) + 2 * h] : kv[4 * j + 2 * h];
          vals[h][j][1] = hh ? kv[4 * (4 + j) + 2 * h + 1] : kv[4 * j + 2 * h + 1];
        }
      if (wg == 1) {
#pragma unroll
        for (int h = 0; h < 2; h++) {
          const int d = (w4 & 1) * 16 + g + h * 8;
#pragma unroll
          for (int j = 0; j < 4; j++)
            *reinterpret_cast<float2*>(red + hh * 1056 + d * 32 + 8 * j + 2 * t) = make_float2(vals[h][j][0], vals[h][j][1]);
          if (t == 0) red[hh * 1056 + 1024 + d] = zz[2 * h];
        }
      }
      named_bar_sync(1, 256);
      if (wg == 0) {
#pragma unroll
        for (int h = 0; h < 2; h++) {
          const int d = (w4 & 1) * 16 + g + h * 8;
#pragma unroll
          for (int j = 0; j < 4; j++) {
            const float2 o = *reinterpret_cast<const float2*>(red + hh * 1056 + d * 32 + 8 * j + 2 * t);
            *reinterpret_cast<float2*>(part + hh * 1056 + d * 32 + 8 * j + 2 * t) = make_float2(vals[h][j][0] + o.x, vals[h][j][1] + o.y);
          }
          if (t == 0) part[hh * 1056 + 1024 + d] = zz[2 * h] + red[hh * 1056 + 1024 + d];
        }
        __threadfence();
        named_bar_sync(2, 128);
        if (tid == 0) atomicAdd(&g_cnt[hp], 1u);
      }
    }
    if (tid == 0) TS(1, 3);
    uint32_t pq[2][4][4];
#pragma unroll
    for (int mb = 0; mb < 2; mb++)
#pragma unroll
      for (int kk = 0; kk < 4; kk++) {
        pq[mb][kk][0] = phi2(acc[mb][8 * kk + 0], acc[mb][8 * kk + 1]);
        pq[mb][kk][1] = phi2(acc[mb][8 * kk + 2], acc[mb][8 * kk + 3]);
        pq[mb][kk][2] = phi2(acc[mb][8 * kk + 4], acc[mb][8 * kk + 5]);
        pq[mb][kk][3] = phi2(acc[mb][8 * kk + 6], acc[mb][8 * kk + 7]);
      }
    if (tid == 0) TS(1, 4);
    if (tid == 0) {
      unsigned int v;
      do { asm volatile("ld.acquire.gpu.global.u32 %0, [%1];" : "=r"(v) : "l"(&g_cnt[hp]) : "memory"); } while (v < 8u);
    }
    named_bar_sync(1, 256);
    {
      if (tid == 0) TS(1, 5);
      const float* pb = g_part + (size_t)(hp * 8) * 2112;
      for (int i = tid; i < 528; i += 256) {
        float4 s4 = make_float4(0.f, 0.f, 0.f, 0.f);
#pragma unroll
        for (int p = 0; p < 8; p++) {
          float4 v4 = __ldcg(reinterpret_cast<const float4*>(pb + p * 2112) + i);
          s4.x += v4.x; s4.y += v4.y; s4.z += v4.z; s4.w += v4.w;
        }
        const int hh = i / 264, rem = i - hh * 264;
        uint8_t* tile = sgen + OFF_KV + hh * 4096;
        if (rem < 256) {
          const int d = rem >> 3, e = (rem & 7) * 4;
          const uint32_t off = d * 128 + (((e >> 3) ^ (d & 7)) << 4) + (e & 7) * 2;
          *reinterpret_cast<uint2*>(tile + off) = make_uint2(pack2(s4.x, s4.y), pack2(s4.z, s4.w));
        } else {
          const int d0 = (rem - 256) * 4;
          float zv[4] = {s4.x, s4.y, s4.z, s4.w};
#pragma unroll
          for (int q = 0; q < 4; q++) {
            const int d = d0 + q;
            const uint32_t off = d * 128 + ((4 ^ (d & 7)) << 4);
            *reinterpret_cast<uint4*>(tile + off) = make_uint4(pack2(zv[q], 0.f), 0u, 0u, 0u);
          }
        }
      }
    }
    fence_async_smem();
    named_bar_sync(1, 256);
    if (tid == 0) TS(1, 6);
#pragma unroll
    for (int mb = 0; mb < 2; mb++) {
#pragma unroll
      for (int hh = 0; hh < 2; hh++) {
        float num[20];
#pragma unroll
        for (int i = 0; i < 20; i++) num[i] = 0.f;
        wg_fence();
#pragma unroll
        for (int kk = 0; kk < 2; kk++) {
          const uint64_t db = make_desc(sbase + OFF_KV + hh * 4096 + kk * 2048, 16, 1024);
          wgmma_rs_n40_tb(num, pq[mb][hh * 2 + kk][0], pq[mb][hh * 2 + kk][1], pq[mb][hh * 2 + kk][2], pq[mb][hh * 2 + kk][3], db, 1);
        }
        wg_commit();
        wg_wait<0>();
        fence_regs(num);
#pragma unroll
        for (int h = 0; h < 2; h++) {
          float den = __shfl_sync(0xffffffffu, num[16 + 2 * h], lane & ~3);
          den = bfr(bfr(den) + 1e-6f);
          const float rden = 1.0f / den;
          const int r = wg * 128 + mb * 64 + w4 * 16 + g + h * 8;
#pragma unroll
          for (int j = 0; j < 4; j++) {
            const uint32_t n2 = pack2(num[4 * j + 2 * h], num[4 * j + 2 * h + 1]);
            const float o0 = lo_f(n2) * rden, o1 = hi_f(n2) * rden;
            const uint32_t off = r * 128 + (((hh * 4 + j) ^ (r & 7)) << 4) + t * 4;
            *reinterpret_cast<uint32_t*>(sgen + OFF_O + off) = pack2(o0, o1);
          }
        }
      }
    }
    named_bar_sync(1, 256);
    if (tid == 0) TS(1, 7);
    for (int i = tid; i < 256 * 8; i += 256) {
      const int r = i >> 3, c = i & 7;
      uint4 v = *reinterpret_cast<const uint4*>(sgen + OFF_O + r * 128 + ((c ^ (r & 7)) << 4));
      *reinterpret_cast<uint4*>(g_o + (size_t)(m0 + r) * DM + hp * 64 + c * 8) = v;
    }
    if (tid == 0) TS(1, 8);
    cluster_sync_all();
  }
}

namespace k3 {
constexpr int BM = 128, BN = 128, BK = 64, ST = 5;
constexpr int A_BYTES = BM * BK * 2, B_BYTES = BK * BN * 2, STAGE = A_BYTES + B_BYTES;
constexpr int OFF_BT = ST * STAGE;
constexpr int OFF_BAR = OFF_BT + 32768;
constexpr int SMEM = OFF_BAR + 1024 + 256;
}

__global__ void __cluster_dims__(2, 1, 1) __launch_bounds__(384, 1)
k3_out(const __grid_constant__ CUtensorMap tmo, const __grid_constant__ CUtensorMap tmw,
       const __grid_constant__ CUtensorMap tmbt, const __grid_constant__ CUtensorMap tmout) {
  using namespace k3;
  extern __shared__ uint8_t smem_raw[];
  const uint32_t sbase = (smem_u32(smem_raw) + 1023) & ~1023u;
  uint8_t* sgen = smem_raw + (sbase - smem_u32(smem_raw));
  const uint32_t bars = sbase + OFF_BAR;
  const uint32_t barbt = bars + 8 * 2 * ST;
  const int tid = threadIdx.x, warp = tid >> 5, lane = tid & 31;
  const uint32_t rank = cluster_ctarank();
  const int cl = blockIdx.x >> 1;
  const int mt = cl >> 2;
  const int nt = ((cl & 3) << 1) + rank;
  const int m0 = mt * BM, n0 = nt * BN;
  if (blockIdx.x == 0 && tid < 16) g_cnt[tid] = 0;

  if (tid == 0) {
    for (int s = 0; s < ST; s++) {
      mbar_init(bars + 8 * s, 1);
      mbar_init(bars + 8 * (ST + s), 16);
    }
    mbar_init(barbt, 1);
    asm volatile("fence.mbarrier_init.release.cluster;" ::: "memory");
  }
  cluster_sync_all();

  if (warp >= 8) {
    asm volatile("setmaxnreg.dec.sync.aligned.u32 40;");
    if (warp == 8 && lane == 0) {
      for (int kb = 0; kb < DM / BK; kb++) {
        const int s = kb % ST;
        mbar_wait(bars + 8 * (ST + s), ((kb / ST) & 1) ^ 1);
        const uint32_t full = bars + 8 * s;
        mbar_expect_tx(full, STAGE);
        const uint32_t sa = sbase + s * STAGE, sb = sa + A_BYTES;
        tma_load_2d_mc(sa + rank * 8192, &tmo, full, kb * BK, m0 + rank * 64, (uint16_t)3);
#pragma unroll
        for (int j = 0; j < 2; j++) tma_load_2d(sb + j * 8192, &tmw, full, n0 + j * 64, kb * BK);
        if (kb == 2) {
          mbar_expect_tx(barbt, 32768);
          tma_load_2d(sbase + OFF_BT, &tmbt, barbt, m0, n0);
          tma_load_2d(sbase + OFF_BT + 16384, &tmbt, barbt, m0 + 64, n0);
        }
      }
    }
    cluster_sync_all();
  } else {
    asm volatile("setmaxnreg.inc.sync.aligned.u32 232;");
    const int wg = warp >> 2, w4 = warp & 3, g = lane >> 2, t = lane & 3;
    if (tid == 0) TS(3, 0);
    float acc[64];
#pragma unroll
    for (int i = 0; i < 64; i++) acc[i] = 0.f;
    for (int kb = 0; kb < DM / BK; kb++) {
      const int s = kb % ST;
      mbar_wait(bars + 8 * s, (kb / ST) & 1);
      const uint32_t sa = sbase + s * STAGE + wg * 8192, sb = sbase + s * STAGE + A_BYTES;
      wg_fence();
#pragma unroll
      for (int ks = 0; ks < 4; ks++) {
        const uint64_t db = make_desc(sb + ks * 2048, 8192, 1024);
        const uint64_t da = make_desc(sa + ks * 32, 16, 1024);
        wgmma_ss_n128_tb(acc, da, db, 1);
      }
      wg_commit();
      if (kb > 0) {
        wg_wait<1>();
        const int sp = (kb - 1) % ST;
        if (lane == 0) { mbar_arrive_cluster(bars + 8 * (ST + sp), 0); mbar_arrive_cluster(bars + 8 * (ST + sp), 1); }
      }
    }
    wg_wait<0>();
    fence_regs(acc);
    if (tid == 0) TS(3, 1);
    named_bar_sync(1, 256);
    mbar_wait(barbt, 0);
#pragma unroll
    for (int h = 0; h < 2; h++) {
      const int rl = wg * 64 + w4 * 16 + g + h * 8;
      const float gt = g_gate[m0 + rl];
      const float omg = bfr(1.0f - gt);
      const uint8_t* bt = sgen + OFF_BT + wg * 16384;
      const int ll = rl & 63;
#pragma unroll
      for (int j = 0; j < 16; j++) {
        const int c = 8 * j + 2 * t;
        const float b0 = __bfloat162float(*reinterpret_cast<const bf16*>(bt + c * 128 + (((ll >> 3) ^ (c & 7)) << 4) + (ll & 7) * 2));
        const float b1 = __bfloat162float(*reinterpret_cast<const bf16*>(bt + (c + 1) * 128 + (((ll >> 3) ^ ((c + 1) & 7)) << 4) + (ll & 7) * 2));
        const uint32_t a2 = pack2(acc[4 * j + 2 * h], acc[4 * j + 2 * h + 1]);
        const float o0 = bfr(gt * lo_f(a2)) + bfr(omg * b0);
        const float o1 = bfr(gt * hi_f(a2)) + bfr(omg * b1);
        *reinterpret_cast<uint32_t*>(sgen + (j >> 3) * 16384 + rl * 128 + (((j & 7) ^ (rl & 7)) << 4) + t * 4) = pack2(o0, o1);
      }
    }
    fence_async_smem();
    if (tid == 0) TS(3, 2);
    named_bar_sync(2 + wg, 128);
    if ((tid & 127) == 0) {
#pragma unroll
      for (int j = 0; j < 2; j++)
        asm volatile("cp.async.bulk.tensor.2d.global.shared::cta.bulk_group [%0, {%2, %3}], [%1];" ::"l"(&tmout),
                     "r"(sbase + j * 16384 + wg * 8192), "r"(n0 + j * 64), "r"(m0 + wg * 64) : "memory");
      asm volatile("cp.async.bulk.commit_group;" ::: "memory");
      asm volatile("cp.async.bulk.wait_group.read 0;" ::: "memory");
      if (tid == 0) TS(3, 3);
    }
    cluster_sync_all();
  }
}

__device__ __align__(1024) bf16 g_bT[DM * SEQ];
constexpr int KOFF = 2048 + 16;
constexpr int KSZ = 2112;
constexpr int KCH = 2 * KSZ + 16;

__device__ __forceinline__ void mma_bf16(float (&d)[4], uint32_t a0, uint32_t a1, uint32_t a2, uint32_t a3, uint32_t b0, uint32_t b1) {
  asm volatile("mma.sync.aligned.m16n8k16.row.col.f32.bf16.bf16.f32 {%0,%1,%2,%3}, {%4,%5,%6,%7}, {%8,%9}, {%0,%1,%2,%3};"
               : "+f"(d[0]), "+f"(d[1]), "+f"(d[2]), "+f"(d[3]) : "r"(a0), "r"(a1), "r"(a2), "r"(a3), "r"(b0), "r"(b1));
}
__device__ __forceinline__ void mma_f16(float (&d)[4], uint32_t a0, uint32_t a1, uint32_t a2, uint32_t a3, uint32_t b0, uint32_t b1) {
  asm volatile("mma.sync.aligned.m16n8k16.row.col.f32.f16.f16.f32 {%0,%1,%2,%3}, {%4,%5,%6,%7}, {%8,%9}, {%0,%1,%2,%3};"
               : "+f"(d[0]), "+f"(d[1]), "+f"(d[2]), "+f"(d[3]) : "r"(a0), "r"(a1), "r"(a2), "r"(a3), "r"(b0), "r"(b1));
}
struct cf { float r, i; };
__device__ __forceinline__ cf cmul(cf a, cf b) { cf c; c.r = a.r * b.r - a.i * b.i; c.i = a.r * b.i + a.i * b.r; return c; }
__device__ __forceinline__ cf csq(cf a) { cf c; c.r = a.r * a.r - a.i * a.i; c.i = 2.f * a.r * a.i; return c; }
__device__ __forceinline__ cf cexpp(float ar, float ai, float p) {
  const float e = ex2f(ar * p * 1.4426950408889634f);
  const float th = ai * p;
  const float k = rintf(th * 0.15915494309189535f);
  float r = fmaf(k, -6.2831854820251465f, th);
  r = fmaf(k, 1.7484556000744e-7f, r);
  cf w; w.r = e * __cosf(r); w.i = e * __sinf(r); return w;
}
__device__ __forceinline__ uint32_t packh(float lo, float hi) {
  uint32_t r; asm("cvt.rn.f16x2.f32 %0, %1, %2;" : "=r"(r) : "f"(hi), "f"(lo)); return r;
}

namespace k2 {
constexpr int CH = 8;
constexpr int UPAD = 128;
constexpr int USZ = UPAD + SEQ;
constexpr int TSTR = 40;
constexpr int TABW = 72 * TSTR;
constexpr int OFF_U = 0;
constexpr int OFF_T = OFF_U + CH * USZ * 2;
constexpr int OFF_K = OFF_T;
constexpr int OFF_Q = OFF_K + CH * KCH * 2;
constexpr int OFF_R = OFF_Q + CH * 2 * 648 * 4;
constexpr int SMEM = OFF_T + 16 * TABW * 4;
static_assert(OFF_R + CH * SEQ * 4 <= SMEM, "smem");
}

__global__ void __launch_bounds__(512, 1)
k2_ssm(const bf16* __restrict__ x, const bf16* __restrict__ logAr, const bf16* __restrict__ Aim, const bf16* __restrict__ Cre,
       const bf16* __restrict__ Cim, const bf16* __restrict__ logdt, const bf16* __restrict__ Dskip,
       const bf16* __restrict__ gatew) {
  using namespace k2;
  extern __shared__ __align__(16) uint8_t sm[];
  const int tid = threadIdx.x, warp = tid >> 5, lane = tid & 31, g = lane >> 2, t = lane & 3;
  const int ch = warp >> 1, half = warp & 1;
  const int d0 = blockIdx.x * CH;
  bf16* us = reinterpret_cast<bf16*>(sm + OFF_U);
  bf16* ks = reinterpret_cast<bf16*>(sm + OFF_K);
  if (tid == 0) TS(2, 0);

  uint4 uv[2][2];
#pragma unroll
  for (int it = 0; it < 2; it++) {
    const int l = 2 * (tid + it * 512);
    uv[it][0] = __ldg(reinterpret_cast<const uint4*>(x + (size_t)l * DM + d0));
    uv[it][1] = __ldg(reinterpret_cast<const uint4*>(x + (size_t)(l + 1) * DM + d0));
  }
  {
    const int r = blockIdx.x * 16 + warp;
    float s = 0.f;
#pragma unroll
    for (int c = lane * 8; c < DM; c += 256) {
      const uint4 xv = __ldg(reinterpret_cast<const uint4*>(x + (size_t)r * DM + c));
      const uint4 wv = __ldg(reinterpret_cast<const uint4*>(gatew + c));
      const bf16* xp = reinterpret_cast<const bf16*>(&xv);
      const bf16* wp = reinterpret_cast<const bf16*>(&wv);
#pragma unroll
      for (int q = 0; q < 8; q++) s += bfr(__bfloat162float(xp[q]) * __bfloat162float(wp[q]));
    }
#pragma unroll
    for (int o = 16; o; o >>= 1) s += __shfl_xor_sync(0xffffffffu, s, o);
    if (lane == 0) { const float z = bfr(s); g_gate[r] = bfr(1.0f / (1.0f + ex2f(-z * 1.4426950408889634f))); }
  }

  float acc[5][4];
#pragma unroll
  for (int a = 0; a < 5; a++)
#pragma unroll
    for (int b = 0; b < 4; b++) acc[a][b] = 0.f;
  float last = 0.f, scale;
  {
    const int d = d0 + ch;
    const float dt = bfr(ex2f(__bfloat162float(logdt[d]) * 1.4426950408889634f));
    float cr[2], ci[2], arr[2], aii[2];
#pragma unroll
    for (int c = 0; c < 2; c++) {
      const int idx = d * NMODE + half * 64 + c * 32 + lane;
      arr[c] = -bfr(ex2f(__bfloat162float(logAr[idx]) * 1.4426950408889634f)) * dt;
      aii[c] = __bfloat162float(Aim[idx]) * dt;
      cr[c] = __bfloat162float(Cre[idx]) * dt;
      ci[c] = __bfloat162float(Cim[idx]) * dt;
    }
    float mx = fmaxf(fmaxf(fabsf(cr[0]), fabsf(ci[0])), fmaxf(fabsf(cr[1]), fabsf(ci[1])));
#pragma unroll
    for (int o = 16; o; o >>= 1) mx = fmaxf(mx, __shfl_xor_sync(0xffffffffu, mx, o));
    {
      int e = (int)((__float_as_uint(mx) >> 23) & 255u) + 1;
      e = e < 32 ? 32 : (e > 220 ? 220 : e);
      scale = __uint_as_float((uint32_t)e << 23);
    }
    const float iscale = __uint_as_float((uint32_t)(254 - ((__float_as_uint(scale) >> 23) & 255u)) << 23);
    uint32_t* tab = reinterpret_cast<uint32_t*>(sm + OFF_T) + warp * TABW;
#pragma unroll 1
    for (int c = 0; c < 2; c++) {
      const float ar = arr[c], ai = aii[c];
      cf C; C.r = cr[c] * iscale; C.i = ci[c] * iscale;
      const cf W1 = cexpp(ar, ai, 1.f), W16 = cexpp(ar, ai, 16.f), W256 = cexpp(ar, ai, 256.f);
      const cf W512 = csq(W256), W1024 = csq(W512);
      const cf W1536 = cmul(W1024, W512);
      {
        const cf w2048 = csq(W1024);
        last += cr[c] * w2048.r - ci[c] * w2048.i;
      }
      uint32_t* tp = tab + lane;
      {
        cf xa = C;
#pragma unroll
        for (int i = 0; i < 16; i++) {
          tp[i * TSTR] = packh(xa.r, -xa.i);
          if ((i & 1) == 0) {
            tp[(16 + i / 2) * TSTR] = packh(xa.r, -xa.i);
            const cf xb = cmul(xa, W256);
            tp[(24 + i / 2) * TSTR] = packh(xb.r, -xb.i);
          }
          xa = cmul(xa, W16);
        }
      }
      {
        cf y; y.r = 1.f; y.i = 0.f;
        const cf W528 = cmul(W512, W16);
        const cf WA16 = cmul(W1024, W16), WB16 = cmul(W1536, W16);
#pragma unroll
        for (int j = 0; j < 16; j++) {
          tp[(32 + j) * TSTR] = packh(y.r, y.i);
          if ((j & 1) == 0) { const cf z = cmul(y, W256); tp[(48 + j / 2) * TSTR] = packh(z.r, z.i); }
          if ((j & 3) == 0) {
            const cf z0 = cmul(y, W512), z1 = cmul(y, W528);
            tp[(56 + j / 4) * TSTR] = packh(z0.r, z0.i);
            tp[(60 + j / 4) * TSTR] = packh(z1.r, z1.i);
          }
          if ((j & 7) == 0) {
            const cf z0 = cmul(y, W1024), z1 = cmul(y, WA16), z2 = cmul(y, W1536), z3 = cmul(y, WB16);
            tp[(64 + j / 8) * TSTR] = packh(z0.r, z0.i);
            tp[(66 + j / 8) * TSTR] = packh(z1.r, z1.i);
            tp[(68 + j / 8) * TSTR] = packh(z2.r, z2.i);
            tp[(70 + j / 8) * TSTR] = packh(z3.r, z3.i);
          }
          y = cmul(y, W1);
        }
      }
      __syncwarp();
#pragma unroll
      for (int ks4 = 0; ks4 < 4; ks4++) {
        const uint32_t* fp = tab + 8 * ks4 + 2 * t;
        const uint2 xa0 = *reinterpret_cast<const uint2*>(fp + g * TSTR), xa1 = *reinterpret_cast<const uint2*>(fp + (g + 8) * TSTR);
        const uint2 xb0 = *reinterpret_cast<const uint2*>(fp + (16 + g) * TSTR), xb1 = *reinterpret_cast<const uint2*>(fp + (24 + g) * TSTR);
        const uint2 y1 = *reinterpret_cast<const uint2*>(fp + (32 + g) * TSTR), y2 = *reinterpret_cast<const uint2*>(fp + (40 + g) * TSTR);
        const uint2 y3 = *reinterpret_cast<const uint2*>(fp + (48 + g) * TSTR), y4 = *reinterpret_cast<const uint2*>(fp + (56 + g) * TSTR);
        const uint2 y5 = *reinterpret_cast<const uint2*>(fp + (64 + g) * TSTR);
        mma_f16(acc[0], xa0.x, xa1.x, xa0.y, xa1.y, y1.x, y1.y);
        mma_f16(acc[1], xa0.x, xa1.x, xa0.y, xa1.y, y2.x, y2.y);
        mma_f16(acc[2], xa0.x, xa1.x, xa0.y, xa1.y, y3.x, y3.y);
        mma_f16(acc[3], xb0.x, xb1.x, xb0.y, xb1.y, y4.x, y4.y);
        mma_f16(acc[4], xb0.x, xb1.x, xb0.y, xb1.y, y5.x, y5.y);
      }
      __syncwarp();
    }
  }
  if (tid == 0) TS(2, 1);
  __syncthreads();
  {
    float* kq = reinterpret_cast<float*>(sm + OFF_Q) + (ch * 2 + half) * 648;
    const float sc2 = 2.f * scale;
#pragma unroll
    for (int h = 0; h < 2; h++) {
      const int i = g + 8 * h;
      *reinterpret_cast<float2*>(kq + 16 * i + 2 * t) = make_float2(sc2 * acc[0][2 * h], sc2 * acc[0][2 * h + 1]);
      *reinterpret_cast<float2*>(kq + 16 * i + 8 + 2 * t) = make_float2(sc2 * acc[1][2 * h], sc2 * acc[1][2 * h + 1]);
      *reinterpret_cast<float2*>(kq + 256 + 8 * i + 2 * t) = make_float2(sc2 * acc[2][2 * h], sc2 * acc[2][2 * h + 1]);
      *reinterpret_cast<float2*>(kq + 384 + 8 * i + 2 * t) = make_float2(sc2 * acc[3][2 * h], sc2 * acc[3][2 * h + 1]);
      *reinterpret_cast<float2*>(kq + 512 + 4 * i + 64 * (t >> 1) + 2 * (t & 1)) = make_float2(sc2 * acc[4][2 * h], sc2 * acc[4][2 * h + 1]);
    }
#pragma unroll
    for (int o = 16; o; o >>= 1) last += __shfl_xor_sync(0xffffffffu, last, o);
    if (lane == 0) kq[640] = 2.f * last;
  }
  if (tid < CH * UPAD / 2) {
    const int c = tid / (UPAD / 2), o = tid % (UPAD / 2);
    reinterpret_cast<uint32_t*>(us + c * USZ)[o] = 0u;
  }
#pragma unroll
  for (int it = 0; it < 2; it++) {
    const int l = 2 * (tid + it * 512);
    const int e = l & 15;
    const int pe = ((e & 7) >> 1) * 4 + (e >> 3) * 2;
    const int pos = UPAD + (l & ~15) + pe;
    const uint32_t a[4] = {uv[it][0].x, uv[it][0].y, uv[it][0].z, uv[it][0].w};
    const uint32_t b[4] = {uv[it][1].x, uv[it][1].y, uv[it][1].z, uv[it][1].w};
#pragma unroll
    for (int c = 0; c < 4; c++) {
      *reinterpret_cast<uint32_t*>(us + (2 * c) * USZ + pos) = __byte_perm(a[c], b[c], 0x5410);
      *reinterpret_cast<uint32_t*>(us + (2 * c + 1) * USZ + pos) = __byte_perm(a[c], b[c], 0x7632);
    }
  }
  named_bar_sync(1 + ch, 64);
  {
    const float* kq0 = reinterpret_cast<const float*>(sm + OFF_Q) + ch * 2 * 648;
    uint32_t* kr = reinterpret_cast<uint32_t*>(ks + ch * KCH);
    uint32_t* kr2 = reinterpret_cast<uint32_t*>(ks + ch * KCH + KSZ + 16);
#pragma unroll 3
    for (int w = half * 528 + lane; w < (half + 1) * 528; w += 32) {
      float kv[3];
#pragma unroll
      for (int q = 0; q < 3; q++) {
        const int xk = KOFF - 2 * w - q;
        float val = 0.f;
        if (xk >= 0 && xk < SEQ) {
          const uint32_t pb = __float_as_uint(bfr((float)xk));
          const int id = xk < 256 ? xk : (256 + ((int)(pb >> 23) - 135) * 128 + (int)((pb >> 16) & 127));
          val = kq0[id] + kq0[648 + id];
        }
        kv[q] = val;
      }
      kr[w] = pack2(kv[0], kv[1]);
      kr2[w] = pack2(kv[1], kv[2]);
    }
  }
  __syncthreads();
  if (tid == 0) TS(2, 2);

  float D[16][4];
#pragma unroll
  for (int j = 0; j < 16; j++)
#pragma unroll
    for (int q = 0; q < 4; q++) D[j][q] = 0.f;
  const bf16* uc = us + ch * USZ + UPAD;
  {
    const bf16* kr = ks + ch * KCH;
    const uint32_t* fbase = reinterpret_cast<const uint32_t*>((g & 1) ? (kr + KSZ + 16) : kr) + ((KOFF - g + 2 * t) >> 1);
    for (int r = half * 4; r < half * 4 + 4; r++) {
      uint32_t B[16][2];
#pragma unroll
      for (int j = 0; j < 16; j++) {
        const uint2 v = *reinterpret_cast<const uint2*>(uc + 16 * (8 * j - r + g) + 4 * t);
        B[j][0] = v.x; B[j][1] = v.y;
      }
      uint32_t fm1 = fbase[-4 * (2 * r - 1)];
#pragma unroll
      for (int k = 0; k < 16; k++) {
        const int dl = 8 * k + r;
        const uint32_t f0 = fbase[-4 * (2 * dl)];
        const uint32_t f1 = fbase[-4 * (2 * dl + 1)];
        if (k > 0) fm1 = fbase[-4 * (2 * dl - 1)];
#pragma unroll
        for (int j = k; j < 16; j++) mma_bf16(D[j], f0, f1, fm1, f0, B[j - k][0], B[j - k][1]);
      }
    }
  }
  if (tid == 0) TS(2, 3);
  float* red = reinterpret_cast<float*>(sm + OFF_R) + ch * SEQ;
#pragma unroll
  for (int j = 0; j < 8; j++) {
    const int jo = half ? j : j + 8;
    *reinterpret_cast<float4*>(red + (jo * 32 + lane) * 4) =
        make_float4(half ? D[j][0] : D[j + 8][0], half ? D[j][1] : D[j + 8][1], half ? D[j][2] : D[j + 8][2], half ? D[j][3] : D[j + 8][3]);
  }
  named_bar_sync(1 + ch, 64);
  {
    const float dsk = __bfloat162float(Dskip[d0 + ch]);
    uint32_t outp[8][2];
#pragma unroll
    for (int j = 0; j < 8; j++) {
      const int jm = half ? j + 8 : j;
      const float4 o = *reinterpret_cast<const float4*>(red + (jm * 32 + lane) * 4);
      const float dd[4] = {(half ? D[j + 8][0] : D[j][0]) + o.x, (half ? D[j + 8][1] : D[j][1]) + o.y,
                           (half ? D[j + 8][2] : D[j][2]) + o.z, (half ? D[j + 8][3] : D[j][3]) + o.w};
      float y[4];
#pragma unroll
      for (int q = 0; q < 4; q++) {
        const int a = 8 * jm + 2 * t + (q & 1), bb = g + (q >> 1) * 8;
        const int pe = ((bb & 7) >> 1) * 4 + (bb >> 3) * 2 + (bb & 1);
        const float uvv = __bfloat162float(uc[16 * a + pe]);
        y[q] = bfr(dd[q]) + bfr(uvv * dsk);
      }
      outp[j][0] = pack2(y[0], y[1]);
      outp[j][1] = pack2(y[2], y[3]);
    }
    named_bar_sync(1 + ch, 64);
    bf16* ys = reinterpret_cast<bf16*>(red);
#pragma unroll
    for (int j = 0; j < 8; j++) {
      const int jm = half ? j + 8 : j;
      const int a = 8 * jm + 2 * t;
      const uint32_t p0 = outp[j][0], p1 = outp[j][1];
      reinterpret_cast<uint16_t*>(ys)[16 * a + g] = (uint16_t)(p0 & 0xffff);
      reinterpret_cast<uint16_t*>(ys)[16 * (a + 1) + g] = (uint16_t)(p0 >> 16);
      reinterpret_cast<uint16_t*>(ys)[16 * a + g + 8] = (uint16_t)(p1 & 0xffff);
      reinterpret_cast<uint16_t*>(ys)[16 * (a + 1) + g + 8] = (uint16_t)(p1 >> 16);
    }
    __syncwarp();
    bf16* dst = g_bT + (size_t)(d0 + ch) * SEQ + half * 1024;
#pragma unroll
    for (int i = 0; i < 4; i++) {
      const uint4 v = *reinterpret_cast<const uint4*>(ys + half * 1024 + (i * 32 + lane) * 8);
      *reinterpret_cast<uint4*>(dst + (i * 32 + lane) * 8) = v;
    }
  }
  if (tid == 0) TS(2, 4);
}

typedef CUresult (*EncodeFn)(CUtensorMap*, CUtensorMapDataType, cuuint32_t, void*, const cuuint64_t*, const cuuint64_t*,
                             const cuuint32_t*, const cuuint32_t*, CUtensorMapInterleave, CUtensorMapSwizzle,
                             CUtensorMapL2promotion, CUtensorMapFloatOOBfill);

static void make_map(EncodeFn enc, CUtensorMap* m, void* ptr, uint64_t inner, uint64_t outer, uint32_t bi, uint32_t bo) {
  cuuint64_t dims[2] = {inner, outer};
  cuuint64_t strides[1] = {inner * 2};
  cuuint32_t box[2] = {bi, bo};
  cuuint32_t es[2] = {1, 1};
  enc(m, CU_TENSOR_MAP_DATA_TYPE_BFLOAT16, 2, ptr, dims, strides, box, es, CU_TENSOR_MAP_INTERLEAVE_NONE,
      CU_TENSOR_MAP_SWIZZLE_128B, CU_TENSOR_MAP_L2_PROMOTION_L2_256B, CU_TENSOR_MAP_FLOAT_OOB_FILL_NONE);
}

extern "C" void kernel_launch(void* const* d_in, const int* in_sizes, int n_in, void* d_out, int out_size) {
  const bf16* x = (const bf16*)d_in[0];
  const bf16* wqkv = (const bf16*)d_in[1];
  const bf16* wo = (const bf16*)d_in[2];
  const bf16* logAr = (const bf16*)d_in[4];
  const bf16* Aim = (const bf16*)d_in[5];
  const bf16* Cre = (const bf16*)d_in[6];
  const bf16* Cim = (const bf16*)d_in[7];
  const bf16* logdt = (const bf16*)d_in[8];
  const bf16* Dskip = (const bf16*)d_in[9];
  const bf16* gatew = (const bf16*)d_in[10];

  static EncodeFn enc = nullptr;
  static void* p_o = nullptr;
  static void* p_bT = nullptr;
  if (!enc) {
    void* fn = nullptr;
    cudaDriverEntryPointQueryResult qr;
    cudaGetDriverEntryPoint("cuTensorMapEncodeTiled", &fn, cudaEnableDefault, &qr);
    enc = (EncodeFn)fn;
    cudaGetSymbolAddress(&p_o, g_o);
    cudaGetSymbolAddress(&p_bT, g_bT);
    cudaFuncSetAttribute(k1_qkv_attn, cudaFuncAttributeMaxDynamicSharedMemorySize, k1::SMEM);
    cudaFuncSetAttribute(k2_ssm, cudaFuncAttributeMaxDynamicSharedMemorySize, k2::SMEM);
    cudaFuncSetAttribute(k3_out, cudaFuncAttributeMaxDynamicSharedMemorySize, k3::SMEM);
  }
  CUtensorMap tmx, tmw, tmo, tmwo, tmbt, tmout;
  make_map(enc, &tmx, (void*)x, 1024, 2048, 64, 128);
  make_map(enc, &tmw, (void*)wqkv, 3072, 1024, 64, 64);
  make_map(enc, &tmo, p_o, 1024, 2048, 64, 64);
  make_map(enc, &tmwo, (void*)wo, 1024, 1024, 64, 64);
  make_map(enc, &tmbt, p_bT, 2048, 1024, 64, 128);
  make_map(enc, &tmout, d_out, 1024, 2048, 64, 64);

  k2_ssm<<<128, 512, k2::SMEM>>>(x, logAr, Aim, Cre, Cim, logdt, Dskip, gatew);
  k1_qkv_attn<<<128, 384, k1::SMEM>>>(tmx, tmw);
  k3_out<<<128, 384, k3::SMEM>>>(tmo, tmwo, tmbt, tmout);
}
```

```cpp
#include <cuda_runtime.h>
#include <cuda_bf16.h>
#include <cuda.h>
#include <stdint.h>

typedef __nv_bfloat16 bf16;

constexpr int SEQ = 2048, DM = 1024, NMODE = 128;

__device__ __align__(1024) bf16 g_o[SEQ * DM];
__device__ __align__(1024) bf16 g_b[SEQ * DM];
__device__ float g_gate[SEQ];
__device__ __align__(16) float g_part[16 * 8 * 2 * 1056];
__device__ unsigned int g_cnt[16];

#define TS(k, i) do {} while (0)
__device__ __forceinline__ uint32_t smem_u32(const void* p) { return (uint32_t)__cvta_generic_to_shared(p); }
__device__ __forceinline__ void mbar_init(uint32_t bar, uint32_t cnt) {
  asm volatile("mbarrier.init.shared::cta.b64 [%0], %1;" ::"r"(bar), "r"(cnt));
}
__device__ __forceinline__ void mbar_expect_tx(uint32_t bar, uint32_t bytes) {
  asm volatile("mbarrier.arrive.expect_tx.shared::cta.b64 _, [%0], %1;" ::"r"(bar), "r"(bytes) : "memory");
}
__device__ __forceinline__ void mbar_arrive_cluster(uint32_t bar, uint32_t cta) {
  asm volatile(
      "{\n.reg .b32 ra;\nmapa.shared::cluster.u32 ra, %0, %1;\n"
      "mbarrier.arrive.shared::cluster.b64 _, [ra];\n}\n" ::"r"(bar), "r"(cta) : "memory");
}
__device__ __forceinline__ bool mbar_try_wait(uint32_t bar, uint32_t parity) {
  uint32_t ok;
  asm volatile(
      "{\n.reg .pred p;\nmbarrier.try_wait.parity.shared::cta.b64 p, [%1], %2;\nselp.u32 %0, 1, 0, p;\n}\n"
      : "=r"(ok) : "r"(bar), "r"(parity) : "memory");
  return ok;
}
__device__ __forceinline__ void mbar_wait(uint32_t bar, uint32_t parity) {
  while (!mbar_try_wait(bar, parity)) {}
}
__device__ __forceinline__ void tma_load_2d(uint32_t dst, const CUtensorMap* map, uint32_t bar, int c0, int c1) {
  asm volatile(
      "cp.async.bulk.tensor.2d.shared::cluster.global.mbarrier::complete_tx::bytes [%0], [%1, {%3, %4}], [%2];" ::"r"(dst),
      "l"(map), "r"(bar), "r"(c0), "r"(c1) : "memory");
}
__device__ __forceinline__ void tma_load_2d_mc(uint32_t dst, const CUtensorMap* map, uint32_t bar, int c0, int c1,
                                               uint16_t mask) {
  asm volatile(
      "cp.async.bulk.tensor.2d.shared::cluster.global.mbarrier::complete_tx::bytes.multicast::cluster [%0], [%1, {%3, %4}], [%2], %5;" ::"r"(dst),
      "l"(map), "r"(bar), "r"(c0), "r"(c1), "h"(mask) : "memory");
}
__device__ __forceinline__ void cluster_sync_all() {
  asm volatile("barrier.cluster.arrive.release.aligned;\nbarrier.cluster.wait.acquire.aligned;\n" ::: "memory");
}
__device__ __forceinline__ uint32_t cluster_ctarank() {
  uint32_t r; asm volatile("mov.u32 %0, %%cluster_ctarank;" : "=r"(r)); return r;
}
__device__ __forceinline__ void pdl_wait() { asm volatile("griddepcontrol.wait;" ::: "memory"); }
__device__ __forceinline__ void pdl_launch() { asm volatile("griddepcontrol.launch_dependents;" ::: "memory"); }
__device__ __forceinline__ void named_bar_sync(int id, int n) { asm volatile("bar.sync %0, %1;" ::"r"(id), "r"(n) : "memory"); }
__device__ __forceinline__ void fence_async_smem() { asm volatile("fence.proxy.async.shared::cta;" ::: "memory"); }
__device__ __forceinline__ void wg_fence() { asm volatile("wgmma.fence.sync.aligned;" ::: "memory"); }
__device__ __forceinline__ void wg_commit() { asm volatile("wgmma.commit_group.sync.aligned;" ::: "memory"); }
template <int N> __device__ __forceinline__ void wg_wait() { asm volatile("wgmma.wait_group.sync.aligned %0;" ::"n"(N) : "memory"); }
__device__ __forceinline__ uint64_t make_desc(uint32_t addr, uint32_t lbo, uint32_t sbo) {
  return (uint64_t)((addr & 0x3FFFF) >> 4) | ((uint64_t)(lbo >> 4) << 16) | ((uint64_t)(sbo >> 4) << 32) | (1ull << 62);
}
__device__ __forceinline__ float bfr(float x) { return __bfloat162float(__float2bfloat16_rn(x)); }
__device__ __forceinline__ uint32_t pack2(float lo, float hi) {
  __nv_bfloat162 v = __floats2bfloat162_rn(lo, hi);
  return *reinterpret_cast<uint32_t*>(&v);
}
__device__ __forceinline__ float ex2f(float x) { float r; asm("ex2.approx.ftz.f32 %0, %1;" : "=f"(r) : "f"(x)); return r; }
__device__ __forceinline__ float lo_f(uint32_t v) { return __uint_as_float(v << 16); }
__device__ __forceinline__ float hi_f(uint32_t v) { return __uint_as_float(v & 0xffff0000u); }
__device__ __forceinline__ uint32_t phi2(float a0, float a1) {
  const uint32_t t2 = pack2(a0, a1);
  const float t0 = lo_f(t2), t1 = hi_f(t2);
  const float e0 = ex2f(t0 * 1.4426950408889634f), e1 = ex2f(t1 * 1.4426950408889634f);
  const float f0 = t0 > 0.f ? t0 + 1.0f : e0;
  const float f1 = t1 > 0.f ? t1 + 1.0f : e1;
  const uint32_t f2 = pack2(f0, f1);
  return pack2(lo_f(f2) + 1e-6f, hi_f(f2) + 1e-6f);
}
template <int R> __device__ __forceinline__ void fence_regs(float (&d)[R]) {
#pragma unroll
  for (int i = 0; i < R; i++) asm volatile("" : "+f"(d[i])::"memory");
}

__device__ __forceinline__ void wgmma_ss_n192_tb(float (&d)[96], uint64_t da, uint64_t db, int sc) {
  asm volatile("{\n.reg .pred p;\nsetp.ne.b32 p, %98, 0;\n"
    "wgmma.mma_async.sync.aligned.m64n192k16.f32.bf16.bf16 {%0, %1, %2, %3, %4, %5, %6, %7, %8, %9, %10, %11, %12, %13, %14, %15, %16, %17, %18, %19, %20, %21, %22, %23, %24, %25, %26, %27, %28, %29, %30, %31, %32, %33, %34, %35, %36, %37, %38, %39, %40, %41, %42, %43, %44, %45, %46, %47, %48, %49, %50, %51, %52, %53, %54, %55, %56, %57, %58, %59, %60, %61, %62, %63, %64, %65, %66, %67, %68, %69, %70, %71, %72, %73, %74, %75, %76, %77, %78, %79, %80, %81, %82, %83, %84, %85, %86, %87, %88, %89, %90, %91, %92, %93, %94, %95}, %96, %97, p, 1, 1, 0, 1;\n}\n"
    : "+f"(d[0]), "+f"(d[1]), "+f"(d[2]), "+f"(d[3]), "+f"(d[4]), "+f"(d[5]), "+f"(d[6]), "+f"(d[7]), "+f"(d[8]), "+f"(d[9]), "+f"(d[10]), "+f"(d[11]), "+f"(d[12]), "+f"(d[13]), "+f"(d[14]), "+f"(d[15]), "+f"(d[16]), "+f"(d[17]), "+f"(d[18]), "+f"(d[19]), "+f"(d[20]), "+f"(d[21]), "+f"(d[22]), "+f"(d[23]), "+f"(d[24]), "+f"(d[25]), "+f"(d[26]), "+f"(d[27]), "+f"(d[28]), "+f"(d[29]), "+f"(d[30]), "+f"(d[31]), "+f"(d[32]), "+f"(d[33]), "+f"(d[34]), "+f"(d[35]), "+f"(d[36]), "+f"(d[37]), "+f"(d[38]), "+f"(d[39]), "+f"(d[40]), "+f"(d[41]), "+f"(d[42]), "+f"(d[43]), "+f"(d[44]), "+f"(d[45]), "+f"(d[46]), "+f"(d[47]), "+f"(d[48]), "+f"(d[49]), "+f"(d[50]), "+f"(d[51]), "+f"(d[52]), "+f"(d[53]), "+f"(d[54]), "+f"(d[55]), "+f"(d[56]), "+f"(d[57]), "+f"(d[58]), "+f"(d[59]), "+f"(d[60]), "+f"(d[61]), "+f"(d[62]), "+f"(d[63]), "+f"(d[64]), "+f"(d[65]), "+f"(d[66]), "+f"(d[67]), "+f"(d[68]), "+f"(d[69]), "+f"(d[70]), "+f"(d[71]), "+f"(d[72]), "+f"(d[73]), "+f"(d[74]), "+f"(d[75]), "+f"(d[76]), "+f"(d[77]), "+f"(d[78]), "+f"(d[79]), "+f"(d[80]), "+f"(d[81]), "+f"(d[82]), "+f"(d[83]), "+f"(d[84]), "+f"(d[85]), "+f"(d[86]), "+f"(d[87]), "+f"(d[88]), "+f"(d[89]), "+f"(d[90]), "+f"(d[91]), "+f"(d[92]), "+f"(d[93]), "+f"(d[94]), "+f"(d[95])
    : "l"(da), "l"(db), "r"(sc));
}

__device__ __forceinline__ void wgmma_ss_n128_tb(float (&d)[64], uint64_t da, uint64_t db, int sc) {
  asm volatile("{\n.reg .pred p;\nsetp.ne.b32 p, %66, 0;\n"
    "wgmma.mma_async.sync.aligned.m64n128k16.f32.bf16.bf16 {%0, %1, %2, %3, %4, %5, %6, %7, %8, %9, %10, %11, %12, %13, %14, %15, %16, %17, %18, %19, %20, %21, %22, %23, %24, %25, %26, %27, %28, %29, %30, %31, %32, %33, %34, %35, %36, %37, %38, %39, %40, %41, %42, %43, %44, %45, %46, %47, %48, %49, %50, %51, %52, %53, %54, %55, %56, %57, %58, %59, %60, %61, %62, %63}, %64, %65, p, 1, 1, 0, 1;\n}\n"
    : "+f"(d[0]), "+f"(d[1]), "+f"(d[2]), "+f"(d[3]), "+f"(d[4]), "+f"(d[5]), "+f"(d[6]), "+f"(d[7]), "+f"(d[8]), "+f"(d[9]), "+f"(d[10]), "+f"(d[11]), "+f"(d[12]), "+f"(d[13]), "+f"(d[14]), "+f"(d[15]), "+f"(d[16]), "+f"(d[17]), "+f"(d[18]), "+f"(d[19]), "+f"(d[20]), "+f"(d[21]), "+f"(d[22]), "+f"(d[23]), "+f"(d[24]), "+f"(d[25]), "+f"(d[26]), "+f"(d[27]), "+f"(d[28]), "+f"(d[29]), "+f"(d[30]), "+f"(d[31]), "+f"(d[32]), "+f"(d[33]), "+f"(d[34]), "+f"(d[35]), "+f"(d[36]), "+f"(d[37]), "+f"(d[38]), "+f"(d[39]), "+f"(d[40]), "+f"(d[41]), "+f"(d[42]), "+f"(d[43]), "+f"(d[44]), "+f"(d[45]), "+f"(d[46]), "+f"(d[47]), "+f"(d[48]), "+f"(d[49]), "+f"(d[50]), "+f"(d[51]), "+f"(d[52]), "+f"(d[53]), "+f"(d[54]), "+f"(d[55]), "+f"(d[56]), "+f"(d[57]), "+f"(d[58]), "+f"(d[59]), "+f"(d[60]), "+f"(d[61]), "+f"(d[62]), "+f"(d[63])
    : "l"(da), "l"(db), "r"(sc));
}

__device__ __forceinline__ void wgmma_ss_n64_tatb(float (&d)[32], uint64_t da, uint64_t db, int sc) {
  asm volatile("{\n.reg .pred p;\nsetp.ne.b32 p, %34, 0;\n"
    "wgmma.mma_async.sync.aligned.m64n64k16.f32.bf16.bf16 {%0, %1, %2, %3, %4, %5, %6, %7, %8, %9, %10, %11, %12, %13, %14, %15, %16, %17, %18, %19, %20, %21, %22, %23, %24, %25, %26, %27, %28, %29, %30, %31}, %32, %33, p, 1, 1, 1, 1;\n}\n"
    : "+f"(d[0]), "+f"(d[1]), "+f"(d[2]), "+f"(d[3]), "+f"(d[4]), "+f"(d[5]), "+f"(d[6]), "+f"(d[7]), "+f"(d[8]), "+f"(d[9]), "+f"(d[10]), "+f"(d[11]), "+f"(d[12]), "+f"(d[13]), "+f"(d[14]), "+f"(d[15]), "+f"(d[16]), "+f"(d[17]), "+f"(d[18]), "+f"(d[19]), "+f"(d[20]), "+f"(d[21]), "+f"(d[22]), "+f"(d[23]), "+f"(d[24]), "+f"(d[25]), "+f"(d[26]), "+f"(d[27]), "+f"(d[28]), "+f"(d[29]), "+f"(d[30]), "+f"(d[31])
    : "l"(da), "l"(db), "r"(sc));
}

__device__ __forceinline__ void wgmma_ss_n8_tatb(float (&d)[4], uint64_t da, uint64_t db, int sc) {
  asm volatile("{\n.reg .pred p;\nsetp.ne.b32 p, %6, 0;\n"
    "wgmma.mma_async.sync.aligned.m64n8k16.f32.bf16.bf16 {%0, %1, %2, %3}, %4, %5, p, 1, 1, 1, 1;\n}\n"
    : "+f"(d[0]), "+f"(d[1]), "+f"(d[2]), "+f"(d[3])
    : "l"(da), "l"(db), "r"(sc));
}

__device__ __forceinline__ void wgmma_rs_n40_tb(float (&d)[20], uint32_t a0, uint32_t a1, uint32_t a2, uint32_t a3, uint64_t db, int sc) {
  asm volatile("{\n.reg .pred p;\nsetp.ne.b32 p, %25, 0;\n"
    "wgmma.mma_async.sync.aligned.m64n40k16.f32.bf16.bf16 {%0, %1, %2, %3, %4, %5, %6, %7, %8, %9, %10, %11, %12, %13, %14, %15, %16, %17, %18, %19}, {%20, %21, %22, %23}, %24, p, 1, 1, 1;\n}\n"
    : "+f"(d[0]), "+f"(d[1]), "+f"(d[2]), "+f"(d[3]), "+f"(d[4]), "+f"(d[5]), "+f"(d[6]), "+f"(d[7]), "+f"(d[8]), "+f"(d[9]), "+f"(d[10]), "+f"(d[11]), "+f"(d[12]), "+f"(d[13]), "+f"(d[14]), "+f"(d[15]), "+f"(d[16]), "+f"(d[17]), "+f"(d[18]), "+f"(d[19])
    : "r"(a0), "r"(a1), "r"(a2), "r"(a3), "l"(db), "r"(sc));
}

namespace k1 {
constexpr int BM = 256, BN = 192, BK = 64, ST = 4;
constexpr int A_BYTES = BM * BK * 2, B_BYTES = BK * BN * 2, STAGE = A_BYTES + B_BYTES;
constexpr int SMEM = ST * STAGE + 1024 + 256;
constexpr int OFF_PK = 0, OFF_V = 32768, OFF_ONES = 65536, OFF_KV = 69632, OFF_O = 81920, OFF_RED = 114688;
}

__global__ void __cluster_dims__(2, 1, 1) __launch_bounds__(384, 1)
k1_qkv_attn(const __grid_constant__ CUtensorMap tmx, const __grid_constant__ CUtensorMap tmw) {
  using namespace k1;
  extern __shared__ uint8_t smem_raw[];
  const uint32_t sbase = (smem_u32(smem_raw) + 1023) & ~1023u;
  uint8_t* sgen = smem_raw + (sbase - smem_u32(smem_raw));
  const uint32_t bars = sbase + ST * STAGE;
  const int tid = threadIdx.x, warp = tid >> 5, lane = tid & 31;
  const uint32_t rank = cluster_ctarank();
  const int cl = blockIdx.x >> 1;
  const int mt = cl >> 3;
  const int hp = ((cl & 7) << 1) + rank;
  const int m0 = mt * BM;

  if (tid == 0) {
    for (int s = 0; s < ST; s++) {
      mbar_init(bars + 8 * s, 1);
      mbar_init(bars + 8 * (ST + s), 16);
    }
    asm volatile("fence.mbarrier_init.release.cluster;" ::: "memory");
  }
  cluster_sync_all();
  pdl_launch();

  if (warp >= 8) {
    asm volatile("setmaxnreg.dec.sync.aligned.u32 40;");
    if (warp == 8 && lane == 0) {
      for (int kb = 0; kb < DM / BK; kb++) {
        const int s = kb % ST;
        mbar_wait(bars + 8 * (ST + s), ((kb / ST) & 1) ^ 1);
        const uint32_t full = bars + 8 * s;
        mbar_expect_tx(full, STAGE);
        const uint32_t sa = sbase + s * STAGE, sb = sa + A_BYTES;
        tma_load_2d_mc(sa + rank * 16384, &tmx, full, kb * BK, m0 + rank * 128, (uint16_t)3);
#pragma unroll
        for (int j = 0; j < 3; j++) tma_load_2d(sb + j * 8192, &tmw, full, j * 1024 + hp * 64, kb * BK);
      }
      pdl_wait();
    }
    cluster_sync_all();
  } else {
    asm volatile("setmaxnreg.inc.sync.aligned.u32 232;");
    const int wg = warp >> 2, w4 = warp & 3, g = lane >> 2, t = lane & 3;
    if (tid == 0) TS(1, 0);
    float acc[2][96];
#pragma unroll
    for (int i = 0; i < 96; i++) { acc[0][i] = 0.f; acc[1][i] = 0.f; }
    for (int kb = 0; kb < DM / BK; kb++) {
      const int s = kb % ST;
      mbar_wait(bars + 8 * s, (kb / ST) & 1);
      const uint32_t sa = sbase + s * STAGE + wg * 16384, sb = sbase + s * STAGE + A_BYTES;
      wg_fence();
#pragma unroll
      for (int ks = 0; ks < 4; ks++) {
        const uint64_t db = make_desc(sb + ks * 2048, 8192, 1024);
#pragma unroll
        for (int mb = 0; mb < 2; mb++) {
          const uint64_t da = make_desc(sa + mb * 8192 + ks * 32, 16, 1024);
          wgmma_ss_n192_tb(acc[mb], da, db, 1);
        }
      }
      wg_commit();
      if (kb > 0) {
        wg_wait<1>();
        const int sp = (kb - 1) % ST;
        if (lane == 0) { mbar_arrive_cluster(bars + 8 * (ST + sp), 0); mbar_arrive_cluster(bars + 8 * (ST + sp), 1); }
      }
    }
    wg_wait<0>();
    fence_regs(acc[0]); fence_regs(acc[1]);
    if (tid == 0) TS(1, 1);
    named_bar_sync(1, 256);

#pragma unroll
    for (int mb = 0; mb < 2; mb++) {
#pragma unroll
      for (int h = 0; h < 2; h++) {
        const int r = wg * 128 + mb * 64 + w4 * 16 + g + h * 8;
#pragma unroll
        for (int j = 0; j < 8; j++) {
          const uint32_t off = r * 128 + ((j ^ (r & 7)) << 4) + t * 4;
          const float k0 = acc[mb][4 * (8 + j) + 2 * h], k1v = acc[mb][4 * (8 + j) + 2 * h + 1];
          const float v0 = acc[mb][4 * (16 + j) + 2 * h], v1 = acc[mb][4 * (16 + j) + 2 * h + 1];
          *reinterpret_cast<uint32_t*>(sgen + OFF_PK + off) = phi2(k0, k1v);
          *reinterpret_cast<uint32_t*>(sgen + OFF_V + off) = pack2(v0, v1);
        }
      }
    }
    if (tid < 256) *reinterpret_cast<uint32_t*>(sgen + OFF_ONES + tid * 4) = 0x3F803F80u;
    fence_async_smem();
    named_bar_sync(1, 256);

    if (tid == 0) TS(1, 2);
    float* part = g_part + (size_t)(hp * 8 + mt) * 2112;
    {
      float kv[32], zz[4];
#pragma unroll
      for (int i = 0; i < 32; i++) kv[i] = 0.f;
#pragma unroll
      for (int i = 0; i < 4; i++) zz[i] = 0.f;
      wg_fence();
#pragma unroll
      for (int ks = 0; ks < 8; ks++) {
        const uint64_t da = make_desc(sbase + OFF_PK + wg * 16384 + ks * 2048, 16, 1024);
        const uint64_t db = make_desc(sbase + OFF_V + wg * 16384 + ks * 2048, 16, 1024);
        const uint64_t d1 = make_desc(sbase + OFF_ONES, 16, 0);
        wgmma_ss_n64_tatb(kv, da, db, 1);
        wgmma_ss_n8_tatb(zz, da, d1, 1);
      }
      wg_commit();
      wg_wait<0>();
      fence_regs(kv); fence_regs(zz);
      const int hh = w4 >> 1;
      float* red = reinterpret_cast<float*>(sgen + OFF_RED);
      float vals[2][4][2];
#pragma unroll
      for (int h = 0; h < 2; h++)
#pragma unroll
        for (int j = 0; j < 4; j++) {
          vals[h][j][0] = hh ? kv[4 * (4 + j) + 2 * h] : kv[4 * j + 2 * h];
          vals[h][j][1] = hh ? kv[4 * (4 + j) + 2 * h + 1] : kv[4 * j + 2 * h + 1];
        }
      if (wg == 1) {
#pragma unroll
        for (int h = 0; h < 2; h++) {
          const int d = (w4 & 1) * 16 + g + h * 8;
#pragma unroll
          for (int j = 0; j < 4; j++)
            *reinterpret_cast<float2*>(red + hh * 1056 + d * 32 + 8 * j + 2 * t) = make_float2(vals[h][j][0], vals[h][j][1]);
          if (t == 0) red[hh * 1056 + 1024 + d] = zz[2 * h];
        }
      }
      named_bar_sync(1, 256);
      if (wg == 0) {
#pragma unroll
        for (int h = 0; h < 2; h++) {
          const int d = (w4 & 1) * 16 + g + h * 8;
#pragma unroll
          for (int j = 0; j < 4; j++) {
            const float2 o = *reinterpret_cast<const float2*>(red + hh * 1056 + d * 32 + 8 * j + 2 * t);
            *reinterpret_cast<float2*>(part + hh * 1056 + d * 32 + 8 * j + 2 * t) = make_float2(vals[h][j][0] + o.x, vals[h][j][1] + o.y);
          }
          if (t == 0) part[hh * 1056 + 1024 + d] = zz[2 * h] + red[hh * 1056 + 1024 + d];
        }
        __threadfence();
        named_bar_sync(2, 128);
        if (tid == 0) atomicAdd(&g_cnt[hp], 1u);
      }
    }
    if (tid == 0) TS(1, 3);
    uint32_t pq[2][4][4];
#pragma unroll
    for (int mb = 0; mb < 2; mb++)
#pragma unroll
      for (int kk = 0; kk < 4; kk++) {
        pq[mb][kk][0] = phi2(acc[mb][8 * kk + 0], acc[mb][8 * kk + 1]);
        pq[mb][kk][1] = phi2(acc[mb][8 * kk + 2], acc[mb][8 * kk + 3]);
        pq[mb][kk][2] = phi2(acc[mb][8 * kk + 4], acc[mb][8 * kk + 5]);
        pq[mb][kk][3] = phi2(acc[mb][8 * kk + 6], acc[mb][8 * kk + 7]);
      }
    if (tid == 0) TS(1, 4);
    if (tid == 0) {
      unsigned int v;
      do { asm volatile("ld.acquire.gpu.global.u32 %0, [%1];" : "=r"(v) : "l"(&g_cnt[hp]) : "memory"); } while (v < 8u);
    }
    named_bar_sync(1, 256);
    {
      if (tid == 0) TS(1, 5);
      const float* pb = g_part + (size_t)(hp * 8) * 2112;
      for (int i = tid; i < 528; i += 256) {
        float4 s4 = make_float4(0.f, 0.f, 0.f, 0.f);
#pragma unroll
        for (int p = 0; p < 8; p++) {
          float4 v4 = __ldcg(reinterpret_cast<const float4*>(pb + p * 2112) + i);
          s4.x += v4.x; s4.y += v4.y; s4.z += v4.z; s4.w += v4.w;
        }
        const int hh = i / 264, rem = i - hh * 264;
        uint8_t* tile = sgen + OFF_KV + hh * 4096;
        if (rem < 256) {
          const int d = rem >> 3, e = (rem & 7) * 4;
          const uint32_t off = d * 128 + (((e >> 3) ^ (d & 7)) << 4) + (e & 7) * 2;
          *reinterpret_cast<uint2*>(tile + off) = make_uint2(pack2(s4.x, s4.y), pack2(s4.z, s4.w));
        } else {
          const int d0 = (rem - 256) * 4;
          float zv[4] = {s4.x, s4.y, s4.z, s4.w};
#pragma unroll
          for (int q = 0; q < 4; q++) {
            const int d = d0 + q;
            const uint32_t off = d * 128 + ((4 ^ (d & 7)) << 4);
            *reinterpret_cast<uint4*>(tile + off) = make_uint4(pack2(zv[q], 0.f), 0u, 0u, 0u);
          }
        }
      }
    }
    fence_async_smem();
    named_bar_sync(1, 256);
    if (tid == 0) TS(1, 6);
#pragma unroll
    for (int mb = 0; mb < 2; mb++) {
#pragma unroll
      for (int hh = 0; hh < 2; hh++) {
        float num[20];
#pragma unroll
        for (int i = 0; i < 20; i++) num[i] = 0.f;
        wg_fence();
#pragma unroll
        for (int kk = 0; kk < 2; kk++) {
          const uint64_t db = make_desc(sbase + OFF_KV + hh * 4096 + kk * 2048, 16, 1024);
          wgmma_rs_n40_tb(num, pq[mb][hh * 2 + kk][0], pq[mb][hh * 2 + kk][1], pq[mb][hh * 2 + kk][2], pq[mb][hh * 2 + kk][3], db, 1);
        }
        wg_commit();
        wg_wait<0>();
        fence_regs(num);
#pragma unroll
        for (int h = 0; h < 2; h++) {
          float den = __shfl_sync(0xffffffffu, num[16 + 2 * h], lane & ~3);
          den = bfr(bfr(den) + 1e-6f);
          const float rden = 1.0f / den;
          const int r = wg * 128 + mb * 64 + w4 * 16 + g + h * 8;
#pragma unroll
          for (int j = 0; j < 4; j++) {
            const uint32_t n2 = pack2(num[4 * j + 2 * h], num[4 * j + 2 * h + 1]);
            const float o0 = lo_f(n2) * rden, o1 = hi_f(n2) * rden;
            const uint32_t off = r * 128 + (((hh * 4 + j) ^ (r & 7)) << 4) + t * 4;
            *reinterpret_cast<uint32_t*>(sgen + OFF_O + off) = pack2(o0, o1);
          }
        }
      }
    }
    named_bar_sync(1, 256);
    if (tid == 0) TS(1, 7);
    for (int i = tid; i < 256 * 8; i += 256) {
      const int r = i >> 3, c = i & 7;
      uint4 v = *reinterpret_cast<const uint4*>(sgen + OFF_O + r * 128 + ((c ^ (r & 7)) << 4));
      *reinterpret_cast<uint4*>(g_o + (size_t)(m0 + r) * DM + hp * 64 + c * 8) = v;
    }
    if (tid == 0) TS(1, 8);
    cluster_sync_all();
  }
}

namespace k3 {
constexpr int BM = 128, BN = 128, BK = 64, ST = 5;
constexpr int A_BYTES = BM * BK * 2, B_BYTES = BK * BN * 2, STAGE = A_BYTES + B_BYTES;
constexpr int OFF_BT = ST * STAGE;
constexpr int OFF_BAR = OFF_BT + 32768;
constexpr int SMEM = OFF_BAR + 1024 + 256;
}

__global__ void __cluster_dims__(2, 1, 1) __launch_bounds__(384, 1)
k3_out(const __grid_constant__ CUtensorMap tmo, const __grid_constant__ CUtensorMap tmw,
       const __grid_constant__ CUtensorMap tmbt, const __grid_constant__ CUtensorMap tmout) {
  using namespace k3;
  extern __shared__ uint8_t smem_raw[];
  const uint32_t sbase = (smem_u32(smem_raw) + 1023) & ~1023u;
  uint8_t* sgen = smem_raw + (sbase - smem_u32(smem_raw));
  const uint32_t bars = sbase + OFF_BAR;
  const uint32_t barbt = bars + 8 * 2 * ST;
  const int tid = threadIdx.x, warp = tid >> 5, lane = tid & 31;
  const uint32_t rank = cluster_ctarank();
  const int cl = blockIdx.x >> 1;
  const int mt = cl >> 2;
  const int nt = ((cl & 3) << 1) + rank;
  const int m0 = mt * BM, n0 = nt * BN;

  if (tid == 0) {
    for (int s = 0; s < ST; s++) {
      mbar_init(bars + 8 * s, 1);
      mbar_init(bars + 8 * (ST + s), 16);
    }
    mbar_init(barbt, 1);
    asm volatile("fence.mbarrier_init.release.cluster;" ::: "memory");
  }
  cluster_sync_all();

  if (warp >= 8) {
    asm volatile("setmaxnreg.dec.sync.aligned.u32 40;");
    if (warp == 8 && lane == 0) {
      for (int kb = 0; kb < ST; kb++) {
        const uint32_t full = bars + 8 * kb;
        mbar_expect_tx(full, STAGE);
        const uint32_t sb = sbase + kb * STAGE + A_BYTES;
#pragma unroll
        for (int j = 0; j < 2; j++) tma_load_2d(sb + j * 8192, &tmw, full, n0 + j * 64, kb * BK);
      }
      pdl_wait();
      if (blockIdx.x == 0) for (int i = 0; i < 16; i++) g_cnt[i] = 0;
      for (int kb = 0; kb < DM / BK; kb++) {
        const int s = kb % ST;
        const uint32_t full = bars + 8 * s;
        const uint32_t sa = sbase + s * STAGE, sb = sa + A_BYTES;
        if (kb >= ST) {
          mbar_wait(bars + 8 * (ST + s), ((kb / ST) & 1) ^ 1);
          mbar_expect_tx(full, STAGE);
#pragma unroll
          for (int j = 0; j < 2; j++) tma_load_2d(sb + j * 8192, &tmw, full, n0 + j * 64, kb * BK);
        }
        tma_load_2d_mc(sa + rank * 8192, &tmo, full, kb * BK, m0 + rank * 64, (uint16_t)3);
        if (kb == 2) {
          mbar_expect_tx(barbt, 32768);
          tma_load_2d(sbase + OFF_BT, &tmbt, barbt, m0, n0);
          tma_load_2d(sbase + OFF_BT + 16384, &tmbt, barbt, m0 + 64, n0);
        }
      }
    }
    cluster_sync_all();
  } else {
    asm volatile("setmaxnreg.inc.sync.aligned.u32 232;");
    const int wg = warp >> 2, w4 = warp & 3, g = lane >> 2, t = lane & 3;
    if (tid == 0) TS(3, 0);
    float acc[64];
#pragma unroll
    for (int i = 0; i < 64; i++) acc[i] = 0.f;
    for (int kb = 0; kb < DM / BK; kb++) {
      const int s = kb % ST;
      mbar_wait(bars + 8 * s, (kb / ST) & 1);
      const uint32_t sa = sbase + s * STAGE + wg * 8192, sb = sbase + s * STAGE + A_BYTES;
      wg_fence();
#pragma unroll
      for (int ks = 0; ks < 4; ks++) {
        const uint64_t db = make_desc(sb + ks * 2048, 8192, 1024);
        const uint64_t da = make_desc(sa + ks * 32, 16, 1024);
        wgmma_ss_n128_tb(acc, da, db, 1);
      }
      wg_commit();
      if (kb > 0) {
        wg_wait<1>();
        const int sp = (kb - 1) % ST;
        if (lane == 0) { mbar_arrive_cluster(bars + 8 * (ST + sp), 0); mbar_arrive_cluster(bars + 8 * (ST + sp), 1); }
      }
    }
    wg_wait<0>();
    fence_regs(acc);
    if (tid == 0) TS(3, 1);
    named_bar_sync(1, 256);
    mbar_wait(barbt, 0);
    pdl_wait();
#pragma unroll
    for (int h = 0; h < 2; h++) {
      const int rl = wg * 64 + w4 * 16 + g + h * 8;
      const float gt = g_gate[m0 + rl];
      const float omg = bfr(1.0f - gt);
      const uint8_t* bt = sgen + OFF_BT + wg * 16384;
      const int ll = rl & 63;
#pragma unroll
      for (int j = 0; j < 16; j++) {
        const int c = 8 * j + 2 * t;
        const float b0 = __bfloat162float(*reinterpret_cast<const bf16*>(bt + c * 128 + (((ll >> 3) ^ (c & 7)) << 4) + (ll & 7) * 2));
        const float b1 = __bfloat162float(*reinterpret_cast<const bf16*>(bt + (c + 1) * 128 + (((ll >> 3) ^ ((c + 1) & 7)) << 4) + (ll & 7) * 2));
        const uint32_t a2 = pack2(acc[4 * j + 2 * h], acc[4 * j + 2 * h + 1]);
        const float o0 = bfr(gt * lo_f(a2)) + bfr(omg * b0);
        const float o1 = bfr(gt * hi_f(a2)) + bfr(omg * b1);
        *reinterpret_cast<uint32_t*>(sgen + (j >> 3) * 16384 + rl * 128 + (((j & 7) ^ (rl & 7)) << 4) + t * 4) = pack2(o0, o1);
      }
    }
    fence_async_smem();
    if (tid == 0) TS(3, 2);
    named_bar_sync(2 + wg, 128);
    if ((tid & 127) == 0) {
#pragma unroll
      for (int j = 0; j < 2; j++)
        asm volatile("cp.async.bulk.tensor.2d.global.shared::cta.bulk_group [%0, {%2, %3}], [%1];" ::"l"(&tmout),
                     "r"(sbase + j * 16384 + wg * 8192), "r"(n0 + j * 64), "r"(m0 + wg * 64) : "memory");
      asm volatile("cp.async.bulk.commit_group;" ::: "memory");
      asm volatile("cp.async.bulk.wait_group.read 0;" ::: "memory");
      if (tid == 0) TS(3, 3);
    }
    cluster_sync_all();
  }
}

__device__ __align__(1024) bf16 g_bT[DM * SEQ];
constexpr int KOFF = 2048 + 16;
constexpr int KSZ = 2112;
constexpr int KCH = 2 * KSZ + 16;

__device__ __forceinline__ void mma_bf16(float (&d)[4], uint32_t a0, uint32_t a1, uint32_t a2, uint32_t a3, uint32_t b0, uint32_t b1) {
  asm volatile("mma.sync.aligned.m16n8k16.row.col.f32.bf16.bf16.f32 {%0,%1,%2,%3}, {%4,%5,%6,%7}, {%8,%9}, {%0,%1,%2,%3};"
               : "+f"(d[0]), "+f"(d[1]), "+f"(d[2]), "+f"(d[3]) : "r"(a0), "r"(a1), "r"(a2), "r"(a3), "r"(b0), "r"(b1));
}
__device__ __forceinline__ void mma_f16(float (&d)[4], uint32_t a0, uint32_t a1, uint32_t a2, uint32_t a3, uint32_t b0, uint32_t b1) {
  asm volatile("mma.sync.aligned.m16n8k16.row.col.f32.f16.f16.f32 {%0,%1,%2,%3}, {%4,%5,%6,%7}, {%8,%9}, {%0,%1,%2,%3};"
               : "+f"(d[0]), "+f"(d[1]), "+f"(d[2]), "+f"(d[3]) : "r"(a0), "r"(a1), "r"(a2), "r"(a3), "r"(b0), "r"(b1));
}
struct cf { float r, i; };
__device__ __forceinline__ cf cmul(cf a, cf b) { cf c; c.r = a.r * b.r - a.i * b.i; c.i = a.r * b.i + a.i * b.r; return c; }
__device__ __forceinline__ cf csq(cf a) { cf c; c.r = a.r * a.r - a.i * a.i; c.i = 2.f * a.r * a.i; return c; }
__device__ __forceinline__ cf cexpp(float ar, float ai, float p) {
  const float e = ex2f(ar * p * 1.4426950408889634f);
  const float th = ai * p;
  const float k = rintf(th * 0.15915494309189535f);
  float r = fmaf(k, -6.2831854820251465f, th);
  r = fmaf(k, 1.7484556000744e-7f, r);
  cf w; w.r = e * __cosf(r); w.i = e * __sinf(r); return w;
}
__device__ __forceinline__ uint32_t packh(float lo, float hi) {
  uint32_t r; asm("cvt.rn.f16x2.f32 %0, %1, %2;" : "=r"(r) : "f"(hi), "f"(lo)); return r;
}

namespace k2 {
constexpr int CH = 8;
constexpr int UPAD = 128;
constexpr int USZ = UPAD + SEQ;
constexpr int TSTR = 40;
constexpr int TABW = 72 * TSTR;
constexpr int OFF_U = 0;
constexpr int OFF_T = OFF_U + CH * USZ * 2;
constexpr int OFF_K = OFF_T;
constexpr int OFF_Q = OFF_K + CH * KCH * 2;
constexpr int OFF_R = OFF_Q + CH * 2 * 648 * 4;
constexpr int SMEM = OFF_T + 16 * TABW * 4;
static_assert(OFF_R + CH * SEQ * 4 <= SMEM, "smem");
}

__global__ void __launch_bounds__(512, 1)
k2_ssm(const bf16* __restrict__ x, const bf16* __restrict__ logAr, const bf16* __restrict__ Aim, const bf16* __restrict__ Cre,
       const bf16* __restrict__ Cim, const bf16* __restrict__ logdt, const bf16* __restrict__ Dskip,
       const bf16* __restrict__ gatew) {
  using namespace k2;
  extern __shared__ __align__(16) uint8_t sm[];
  const int tid = threadIdx.x, warp = tid >> 5, lane = tid & 31, g = lane >> 2, t = lane & 3;
  const int ch = warp >> 1, half = warp & 1;
  const int d0 = blockIdx.x * CH;
  bf16* us = reinterpret_cast<bf16*>(sm + OFF_U);
  bf16* ks = reinterpret_cast<bf16*>(sm + OFF_K);
  if (tid == 0) TS(2, 0);
  pdl_launch();

  uint4 uv[2][2];
#pragma unroll
  for (int it = 0; it < 2; it++) {
    const int l = 2 * (tid + it * 512);
    uv[it][0] = __ldg(reinterpret_cast<const uint4*>(x + (size_t)l * DM + d0));
    uv[it][1] = __ldg(reinterpret_cast<const uint4*>(x + (size_t)(l + 1) * DM + d0));
  }
  {
    const int r = blockIdx.x * 16 + warp;
    float s = 0.f;
#pragma unroll
    for (int c = lane * 8; c < DM; c += 256) {
      const uint4 xv = __ldg(reinterpret_cast<const uint4*>(x + (size_t)r * DM + c));
      const uint4 wv = __ldg(reinterpret_cast<const uint4*>(gatew + c));
      const bf16* xp = reinterpret_cast<const bf16*>(&xv);
      const bf16* wp = reinterpret_cast<const bf16*>(&wv);
#pragma unroll
      for (int q = 0; q < 8; q++) s += bfr(__bfloat162float(xp[q]) * __bfloat162float(wp[q]));
    }
#pragma unroll
    for (int o = 16; o; o >>= 1) s += __shfl_xor_sync(0xffffffffu, s, o);
    if (lane == 0) { const float z = bfr(s); g_gate[r] = bfr(1.0f / (1.0f + ex2f(-z * 1.4426950408889634f))); }
  }

  float acc[5][4];
#pragma unroll
  for (int a = 0; a < 5; a++)
#pragma unroll
    for (int b = 0; b < 4; b++) acc[a][b] = 0.f;
  float last = 0.f, scale;
  {
    const int d = d0 + ch;
    const float dt = bfr(ex2f(__bfloat162float(logdt[d]) * 1.4426950408889634f));
    float cr[2], ci[2], arr[2], aii[2];
#pragma unroll
    for (int c = 0; c < 2; c++) {
      const int idx = d * NMODE + half * 64 + c * 32 + lane;
      arr[c] = -bfr(ex2f(__bfloat162float(logAr[idx]) * 1.4426950408889634f)) * dt;
      aii[c] = __bfloat162float(Aim[idx]) * dt;
      cr[c] = __bfloat162float(Cre[idx]) * dt;
      ci[c] = __bfloat162float(Cim[idx]) * dt;
    }
    float mx = fmaxf(fmaxf(fabsf(cr[0]), fabsf(ci[0])), fmaxf(fabsf(cr[1]), fabsf(ci[1])));
#pragma unroll
    for (int o = 16; o; o >>= 1) mx = fmaxf(mx, __shfl_xor_sync(0xffffffffu, mx, o));
    {
      int e = (int)((__float_as_uint(mx) >> 23) & 255u) + 1;
      e = e < 32 ? 32 : (e > 220 ? 220 : e);
      scale = __uint_as_float((uint32_t)e << 23);
    }
    const float iscale = __uint_as_float((uint32_t)(254 - ((__float_as_uint(scale) >> 23) & 255u)) << 23);
    uint32_t* tab = reinterpret_cast<uint32_t*>(sm + OFF_T) + warp * TABW;
#pragma unroll 1
    for (int c = 0; c < 2; c++) {
      const float ar = arr[c], ai = aii[c];
      cf C; C.r = cr[c] * iscale; C.i = ci[c] * iscale;
      const cf W1 = cexpp(ar, ai, 1.f), W16 = cexpp(ar, ai, 16.f), W256 = cexpp(ar, ai, 256.f);
      const cf W512 = csq(W256), W1024 = csq(W512);
      const cf W1536 = cmul(W1024, W512);
      {
        const cf w2048 = csq(W1024);
        last += cr[c] * w2048.r - ci[c] * w2048.i;
      }
      uint32_t* tp = tab + lane;
      {
        cf xa = C;
#pragma unroll
        for (int i = 0; i < 16; i++) {
          tp[i * TSTR] = packh(xa.r, -xa.i);
          if ((i & 1) == 0) {
            tp[(16 + i / 2) * TSTR] = packh(xa.r, -xa.i);
            const cf xb = cmul(xa, W256);
            tp[(24 + i / 2) * TSTR] = packh(xb.r, -xb.i);
          }
          xa = cmul(xa, W16);
        }
      }
      {
        cf y; y.r = 1.f; y.i = 0.f;
        const cf W528 = cmul(W512, W16);
        const cf WA16 = cmul(W1024, W16), WB16 = cmul(W1536, W16);
#pragma unroll
        for (int j = 0; j < 16; j++) {
          tp[(32 + j) * TSTR] = packh(y.r, y.i);
          if ((j & 1) == 0) { const cf z = cmul(y, W256); tp[(48 + j / 2) * TSTR] = packh(z.r, z.i); }
          if ((j & 3) == 0) {
            const cf z0 = cmul(y, W512), z1 = cmul(y, W528);
            tp[(56 + j / 4) * TSTR] = packh(z0.r, z0.i);
            tp[(60 + j / 4) * TSTR] = packh(z1.r, z1.i);
          }
          if ((j & 7) == 0) {
            const cf z0 = cmul(y, W1024), z1 = cmul(y, WA16), z2 = cmul(y, W1536), z3 = cmul(y, WB16);
            tp[(64 + j / 8) * TSTR] = packh(z0.r, z0.i);
            tp[(66 + j / 8) * TSTR] = packh(z1.r, z1.i);
            tp[(68 + j / 8) * TSTR] = packh(z2.r, z2.i);
            tp[(70 + j / 8) * TSTR] = packh(z3.r, z3.i);
          }
          y = cmul(y, W1);
        }
      }
      __syncwarp();
#pragma unroll
      for (int ks4 = 0; ks4 < 4; ks4++) {
        const uint32_t* fp = tab + 8 * ks4 + 2 * t;
        const uint2 xa0 = *reinterpret_cast<const uint2*>(fp + g * TSTR), xa1 = *reinterpret_cast<const uint2*>(fp + (g + 8) * TSTR);
        const uint2 xb0 = *reinterpret_cast<const uint2*>(fp + (16 + g) * TSTR), xb1 = *reinterpret_cast<const uint2*>(fp + (24 + g) * TSTR);
        const uint2 y1 = *reinterpret_cast<const uint2*>(fp + (32 + g) * TSTR), y2 = *reinterpret_cast<const uint2*>(fp + (40 + g) * TSTR);
        const uint2 y3 = *reinterpret_cast<const uint2*>(fp + (48 + g) * TSTR), y4 = *reinterpret_cast<const uint2*>(fp + (56 + g) * TSTR);
        const uint2 y5 = *reinterpret_cast<const uint2*>(fp + (64 + g) * TSTR);
        mma_f16(acc[0], xa0.x, xa1.x, xa0.y, xa1.y, y1.x, y1.y);
        mma_f16(acc[1], xa0.x, xa1.x, xa0.y, xa1.y, y2.x, y2.y);
        mma_f16(acc[2], xa0.x, xa1.x, xa0.y, xa1.y, y3.x, y3.y);
        mma_f16(acc[3], xb0.x, xb1.x, xb0.y, xb1.y, y4.x, y4.y);
        mma_f16(acc[4], xb0.x, xb1.x, xb0.y, xb1.y, y5.x, y5.y);
      }
      __syncwarp();
    }
  }
  if (tid == 0) TS(2, 1);
  __syncthreads();
  {
    float* kq = reinterpret_cast<float*>(sm + OFF_Q) + (ch * 2 + half) * 648;
    const float sc2 = 2.f * scale;
#pragma unroll
    for (int h = 0; h < 2; h++) {
      const int i = g + 8 * h;
      *reinterpret_cast<float2*>(kq + 16 * i + 2 * t) = make_float2(sc2 * acc[0][2 * h], sc2 * acc[0][2 * h + 1]);
      *reinterpret_cast<float2*>(kq + 16 * i + 8 + 2 * t) = make_float2(sc2 * acc[1][2 * h], sc2 * acc[1][2 * h + 1]);
      *reinterpret_cast<float2*>(kq + 256 + 8 * i + 2 * t) = make_float2(sc2 * acc[2][2 * h], sc2 * acc[2][2 * h + 1]);
      *reinterpret_cast<float2*>(kq + 384 + 8 * i + 2 * t) = make_float2(sc2 * acc[3][2 * h], sc2 * acc[3][2 * h + 1]);
      *reinterpret_cast<float2*>(kq + 512 + 4 * i + 64 * (t >> 1) + 2 * (t & 1)) = make_float2(sc2 * acc[4][2 * h], sc2 * acc[4][2 * h + 1]);
    }
#pragma unroll
    for (int o = 16; o; o >>= 1) last += __shfl_xor_sync(0xffffffffu, last, o);
    if (lane == 0) kq[640] = 2.f * last;
  }
  if (tid < CH * UPAD / 2) {
    const int c = tid / (UPAD / 2), o = tid % (UPAD / 2);
    reinterpret_cast<uint32_t*>(us + c * USZ)[o] = 0u;
  }
#pragma unroll
  for (int it = 0; it < 2; it++) {
    const int l = 2 * (tid + it * 512);
    const int e = l & 15;
    const int pe = ((e & 7) >> 1) * 4 + (e >> 3) * 2;
    const int pos = UPAD + (l & ~15) + pe;
    const uint32_t a[4] = {uv[it][0].x, uv[it][0].y, uv[it][0].z, uv[it][0].w};
    const uint32_t b[4] = {uv[it][1].x, uv[it][1].y, uv[it][1].z, uv[it][1].w};
#pragma unroll
    for (int c = 0; c < 4; c++) {
      *reinterpret_cast<uint32_t*>(us + (2 * c) * USZ + pos) = __byte_perm(a[c], b[c], 0x5410);
      *reinterpret_cast<uint32_t*>(us + (2 * c + 1) * USZ + pos) = __byte_perm(a[c], b[c], 0x7632);
    }
  }
  named_bar_sync(1 + ch, 64);
  {
    const float* kq0 = reinterpret_cast<const float*>(sm + OFF_Q) + ch * 2 * 648;
    uint32_t* kr = reinterpret_cast<uint32_t*>(ks + ch * KCH);
    uint32_t* kr2 = reinterpret_cast<uint32_t*>(ks + ch * KCH + KSZ + 16);
#pragma unroll 3
    for (int w = half * 528 + lane; w < (half + 1) * 528; w += 32) {
      float kv[3];
#pragma unroll
      for (int q = 0; q < 3; q++) {
        const int xk = KOFF - 2 * w - q;
        float val = 0.f;
        if (xk >= 0 && xk < SEQ) {
          const uint32_t pb = __float_as_uint(bfr((float)xk));
          const int id = xk < 256 ? xk : (256 + ((int)(pb >> 23) - 135) * 128 + (int)((pb >> 16) & 127));
          val = kq0[id] + kq0[648 + id];
        }
        kv[q] = val;
      }
      kr[w] = pack2(kv[0], kv[1]);
      kr2[w] = pack2(kv[1], kv[2]);
    }
  }
  __syncthreads();
  if (tid == 0) TS(2, 2);

  float D[16][4];
#pragma unroll
  for (int j = 0; j < 16; j++)
#pragma unroll
    for (int q = 0; q < 4; q++) D[j][q] = 0.f;
  const bf16* uc = us + ch * USZ + UPAD;
  {
    const bf16* kr = ks + ch * KCH;
    const uint32_t* fbase = reinterpret_cast<const uint32_t*>((g & 1) ? (kr + KSZ + 16) : kr) + ((KOFF - g + 2 * t) >> 1);
    for (int r = half * 4; r < half * 4 + 4; r++) {
      uint32_t B[16][2];
#pragma unroll
      for (int j = 0; j < 16; j++) {
        const uint2 v = *reinterpret_cast<const uint2*>(uc + 16 * (8 * j - r + g) + 4 * t);
        B[j][0] = v.x; B[j][1] = v.y;
      }
      uint32_t fm1 = fbase[-4 * (2 * r - 1)];
#pragma unroll
      for (int k = 0; k < 16; k++) {
        const int dl = 8 * k + r;
        const uint32_t f0 = fbase[-4 * (2 * dl)];
        const uint32_t f1 = fbase[-4 * (2 * dl + 1)];
        if (k > 0) fm1 = fbase[-4 * (2 * dl - 1)];
#pragma unroll
        for (int j = k; j < 16; j++) mma_bf16(D[j], f0, f1, fm1, f0, B[j - k][0], B[j - k][1]);
      }
    }
  }
  if (tid == 0) TS(2, 3);
  float* red = reinterpret_cast<float*>(sm + OFF_R) + ch * SEQ;
#pragma unroll
  for (int j = 0; j < 8; j++) {
    const int jo = half ? j : j + 8;
    *reinterpret_cast<float4*>(red + (jo * 32 + lane) * 4) =
        make_float4(half ? D[j][0] : D[j + 8][0], half ? D[j][1] : D[j + 8][1], half ? D[j][2] : D[j + 8][2], half ? D[j][3] : D[j + 8][3]);
  }
  named_bar_sync(1 + ch, 64);
  {
    const float dsk = __bfloat162float(Dskip[d0 + ch]);
    uint32_t outp[8][2];
#pragma unroll
    for (int j = 0; j < 8; j++) {
      const int jm = half ? j + 8 : j;
      const float4 o = *reinterpret_cast<const float4*>(red + (jm * 32 + lane) * 4);
      const float dd[4] = {(half ? D[j + 8][0] : D[j][0]) + o.x, (half ? D[j + 8][1] : D[j][1]) + o.y,
                           (half ? D[j + 8][2] : D[j][2]) + o.z, (half ? D[j + 8][3] : D[j][3]) + o.w};
      float y[4];
#pragma unroll
      for (int q = 0; q < 4; q++) {
        const int a = 8 * jm + 2 * t + (q & 1), bb = g + (q >> 1) * 8;
        const int pe = ((bb & 7) >> 1) * 4 + (bb >> 3) * 2 + (bb & 1);
        const float uvv = __bfloat162float(uc[16 * a + pe]);
        y[q] = bfr(dd[q]) + bfr(uvv * dsk);
      }
      outp[j][0] = pack2(y[0], y[1]);
      outp[j][1] = pack2(y[2], y[3]);
    }
    named_bar_sync(1 + ch, 64);
    bf16* ys = reinterpret_cast<bf16*>(red);
#pragma unroll
    for (int j = 0; j < 8; j++) {
      const int jm = half ? j + 8 : j;
      const int a = 8 * jm + 2 * t;
      const uint32_t p0 = outp[j][0], p1 = outp[j][1];
      reinterpret_cast<uint16_t*>(ys)[16 * a + g] = (uint16_t)(p0 & 0xffff);
      reinterpret_cast<uint16_t*>(ys)[16 * (a + 1) + g] = (uint16_t)(p0 >> 16);
      reinterpret_cast<uint16_t*>(ys)[16 * a + g + 8] = (uint16_t)(p1 & 0xffff);
      reinterpret_cast<uint16_t*>(ys)[16 * (a + 1) + g + 8] = (uint16_t)(p1 >> 16);
    }
    __syncwarp();
    bf16* dst = g_bT + (size_t)(d0 + ch) * SEQ + half * 1024;
#pragma unroll
    for (int i = 0; i < 4; i++) {
      const uint4 v = *reinterpret_cast<const uint4*>(ys + half * 1024 + (i * 32 + lane) * 8);
      *reinterpret_cast<uint4*>(dst + (i * 32 + lane) * 8) = v;
    }
  }
  if (tid == 0) TS(2, 4);
}

typedef CUresult (*EncodeFn)(CUtensorMap*, CUtensorMapDataType, cuuint32_t, void*, const cuuint64_t*, const cuuint64_t*,
                             const cuuint32_t*, const cuuint32_t*, CUtensorMapInterleave, CUtensorMapSwizzle,
                             CUtensorMapL2promotion, CUtensorMapFloatOOBfill);

static void make_map(EncodeFn enc, CUtensorMap* m, void* ptr, uint64_t inner, uint64_t outer, uint32_t bi, uint32_t bo) {
  cuuint64_t dims[2] = {inner, outer};
  cuuint64_t strides[1] = {inner * 2};
  cuuint32_t box[2] = {bi, bo};
  cuuint32_t es[2] = {1, 1};
  enc(m, CU_TENSOR_MAP_DATA_TYPE_BFLOAT16, 2, ptr, dims, strides, box, es, CU_TENSOR_MAP_INTERLEAVE_NONE,
      CU_TENSOR_MAP_SWIZZLE_128B, CU_TENSOR_MAP_L2_PROMOTION_L2_256B, CU_TENSOR_MAP_FLOAT_OOB_FILL_NONE);
}

extern "C" void kernel_launch(void* const* d_in, const int* in_sizes, int n_in, void* d_out, int out_size) {
  const bf16* x = (const bf16*)d_in[0];
  const bf16* wqkv = (const bf16*)d_in[1];
  const bf16* wo = (const bf16*)d_in[2];
  const bf16* logAr = (const bf16*)d_in[4];
  const bf16* Aim = (const bf16*)d_in[5];
  const bf16* Cre = (const bf16*)d_in[6];
  const bf16* Cim = (const bf16*)d_in[7];
  const bf16* logdt = (const bf16*)d_in[8];
  const bf16* Dskip = (const bf16*)d_in[9];
  const bf16* gatew = (const bf16*)d_in[10];

  static EncodeFn enc = nullptr;
  static void* p_o = nullptr;
  static void* p_bT = nullptr;
  if (!enc) {
    void* fn = nullptr;
    cudaDriverEntryPointQueryResult qr;
    cudaGetDriverEntryPoint("cuTensorMapEncodeTiled", &fn, cudaEnableDefault, &qr);
    enc = (EncodeFn)fn;
    cudaGetSymbolAddress(&p_o, g_o);
    cudaGetSymbolAddress(&p_bT, g_bT);
    cudaFuncSetAttribute(k1_qkv_attn, cudaFuncAttributeMaxDynamicSharedMemorySize, k1::SMEM);
    cudaFuncSetAttribute(k2_ssm, cudaFuncAttributeMaxDynamicSharedMemorySize, k2::SMEM);
    cudaFuncSetAttribute(k3_out, cudaFuncAttributeMaxDynamicSharedMemorySize, k3::SMEM);
  }
  CUtensorMap tmx, tmw, tmo, tmwo, tmbt, tmout;
  make_map(enc, &tmx, (void*)x, 1024, 2048, 64, 128);
  make_map(enc, &tmw, (void*)wqkv, 3072, 1024, 64, 64);
  make_map(enc, &tmo, p_o, 1024, 2048, 64, 64);
  make_map(enc, &tmwo, (void*)wo, 1024, 1024, 64, 64);
  make_map(enc, &tmbt, p_bT, 2048, 1024, 64, 128);
  make_map(enc, &tmout, d_out, 1024, 2048, 64, 64);

  k2_ssm<<<128, 512, k2::SMEM>>>(x, logAr, Aim, Cre, Cim, logdt, Dskip, gatew);
  cudaLaunchAttribute at[1];
  at[0].id = cudaLaunchAttributeProgrammaticStreamSerialization;
  at[0].val.programmaticStreamSerializationAllowed = 1;
  cudaLaunchConfig_t cfg = {};
  cfg.gridDim = dim3(128); cfg.blockDim = dim3(384); cfg.stream = cudaStreamPerThread; cfg.attrs = at; cfg.numAttrs = 1;
  cfg.dynamicSmemBytes = k1::SMEM;
  cudaLaunchKernelEx(&cfg, k1_qkv_attn, tmx, tmw);
  cfg.dynamicSmemBytes = k3::SMEM;
  cudaLaunchKernelEx(&cfg, k3_out, tmo, tmwo, tmbt, tmout);
}
```

```cpp
#include <cuda_runtime.h>
#include <cuda_bf16.h>
#include <cuda.h>
#include <stdint.h>

typedef __nv_bfloat16 bf16;

constexpr int SEQ = 2048, DM = 1024, NMODE = 128;

__device__ __align__(1024) bf16 g_o[SEQ * DM];
__device__ __align__(1024) bf16 g_b[SEQ * DM];
__device__ float g_gate[SEQ];
__device__ __align__(16) float g_part[16 * 8 * 2 * 1056];
__device__ unsigned int g_cnt[16];

#define TS(k, i) do {} while (0)
__device__ __forceinline__ uint32_t smem_u32(const void* p) { return (uint32_t)__cvta_generic_to_shared(p); }
__device__ __forceinline__ void mbar_init(uint32_t bar, uint32_t cnt) {
  asm volatile("mbarrier.init.shared::cta.b64 [%0], %1;" ::"r"(bar), "r"(cnt));
}
__device__ __forceinline__ void mbar_expect_tx(uint32_t bar, uint32_t bytes) {
  asm volatile("mbarrier.arrive.expect_tx.shared::cta.b64 _, [%0], %1;" ::"r"(bar), "r"(bytes) : "memory");
}
__device__ __forceinline__ void mbar_arrive_cluster(uint32_t bar, uint32_t cta) {
  asm volatile(
      "{\n.reg .b32 ra;\nmapa.shared::cluster.u32 ra, %0, %1;\n"
      "mbarrier.arrive.shared::cluster.b64 _, [ra];\n}\n" ::"r"(bar), "r"(cta) : "memory");
}
__device__ __forceinline__ bool mbar_try_wait(uint32_t bar, uint32_t parity) {
  uint32_t ok;
  asm volatile(
      "{\n.reg .pred p;\nmbarrier.try_wait.parity.shared::cta.b64 p, [%1], %2;\nselp.u32 %0, 1, 0, p;\n}\n"
      : "=r"(ok) : "r"(bar), "r"(parity) : "memory");
  return ok;
}
__device__ __forceinline__ void mbar_wait(uint32_t bar, uint32_t parity) {
  while (!mbar_try_wait(bar, parity)) {}
}
__device__ __forceinline__ void tma_load_2d(uint32_t dst, const CUtensorMap* map, uint32_t bar, int c0, int c1) {
  asm volatile(
      "cp.async.bulk.tensor.2d.shared::cluster.global.mbarrier::complete_tx::bytes [%0], [%1, {%3, %4}], [%2];" ::"r"(dst),
      "l"(map), "r"(bar), "r"(c0), "r"(c1) : "memory");
}
__device__ __forceinline__ void tma_load_2d_mc(uint32_t dst, const CUtensorMap* map, uint32_t bar, int c0, int c1,
                                               uint16_t mask) {
  asm volatile(
      "cp.async.bulk.tensor.2d.shared::cluster.global.mbarrier::complete_tx::bytes.multicast::cluster [%0], [%1, {%3, %4}], [%2], %5;" ::"r"(dst),
      "l"(map), "r"(bar), "r"(c0), "r"(c1), "h"(mask) : "memory");
}
__device__ __forceinline__ void cluster_sync_all() {
  asm volatile("barrier.cluster.arrive.release.aligned;\nbarrier.cluster.wait.acquire.aligned;\n" ::: "memory");
}
__device__ __forceinline__ uint32_t cluster_ctarank() {
  uint32_t r; asm volatile("mov.u32 %0, %%cluster_ctarank;" : "=r"(r)); return r;
}
__device__ __forceinline__ void pdl_wait() { asm volatile("griddepcontrol.wait;" ::: "memory"); }
__device__ __forceinline__ void pdl_launch() { asm volatile("griddepcontrol.launch_dependents;" ::: "memory"); }
__device__ __forceinline__ void named_bar_sync(int id, int n) { asm volatile("bar.sync %0, %1;" ::"r"(id), "r"(n) : "memory"); }
__device__ __forceinline__ void fence_async_smem() { asm volatile("fence.proxy.async.shared::cta;" ::: "memory"); }
__device__ __forceinline__ void wg_fence() { asm volatile("wgmma.fence.sync.aligned;" ::: "memory"); }
__device__ __forceinline__ void wg_commit() { asm volatile("wgmma.commit_group.sync.aligned;" ::: "memory"); }
template <int N> __device__ __forceinline__ void wg_wait() { asm volatile("wgmma.wait_group.sync.aligned %0;" ::"n"(N) : "memory"); }
__device__ __forceinline__ uint64_t make_desc(uint32_t addr, uint32_t lbo, uint32_t sbo) {
  return (uint64_t)((addr & 0x3FFFF) >> 4) | ((uint64_t)(lbo >> 4) << 16) | ((uint64_t)(sbo >> 4) << 32) | (1ull << 62);
}
__device__ __forceinline__ float bfr(float x) { return __bfloat162float(__float2bfloat16_rn(x)); }
__device__ __forceinline__ uint32_t pack2(float lo, float hi) {
  __nv_bfloat162 v = __floats2bfloat162_rn(lo, hi);
  return *reinterpret_cast<uint32_t*>(&v);
}
__device__ __forceinline__ float ex2f(float x) { float r; asm("ex2.approx.ftz.f32 %0, %1;" : "=f"(r) : "f"(x)); return r; }
__device__ __forceinline__ float lo_f(uint32_t v) { return __uint_as_float(v << 16); }
__device__ __forceinline__ float hi_f(uint32_t v) { return __uint_as_float(v & 0xffff0000u); }
__device__ __forceinline__ uint32_t phi2(float a0, float a1) {
  const uint32_t t2 = pack2(a0, a1);
  const float t0 = lo_f(t2), t1 = hi_f(t2);
  const float e0 = ex2f(t0 * 1.4426950408889634f), e1 = ex2f(t1 * 1.4426950408889634f);
  const float f0 = t0 > 0.f ? t0 + 1.0f : e0;
  const float f1 = t1 > 0.f ? t1 + 1.0f : e1;
  const uint32_t f2 = pack2(f0, f1);
  return pack2(lo_f(f2) + 1e-6f, hi_f(f2) + 1e-6f);
}
template <int R> __device__ __forceinline__ void fence_regs(float (&d)[R]) {
#pragma unroll
  for (int i = 0; i < R; i++) asm volatile("" : "+f"(d[i])::"memory");
}

__device__ __forceinline__ void wgmma_ss_n192_tb(float (&d)[96], uint64_t da, uint64_t db, int sc) {
  asm volatile("{\n.reg .pred p;\nsetp.ne.b32 p, %98, 0;\n"
    "wgmma.mma_async.sync.aligned.m64n192k16.f32.bf16.bf16 {%0, %1, %2, %3, %4, %5, %6, %7, %8, %9, %10, %11, %12, %13, %14, %15, %16, %17, %18, %19, %20, %21, %22, %23, %24, %25, %26, %27, %28, %29, %30, %31, %32, %33, %34, %35, %36, %37, %38, %39, %40, %41, %42, %43, %44, %45, %46, %47, %48, %49, %50, %51, %52, %53, %54, %55, %56, %57, %58, %59, %60, %61, %62, %63, %64, %65, %66, %67, %68, %69, %70, %71, %72, %73, %74, %75, %76, %77, %78, %79, %80, %81, %82, %83, %84, %85, %86, %87, %88, %89, %90, %91, %92, %93, %94, %95}, %96, %97, p, 1, 1, 0, 1;\n}\n"
    : "+f"(d[0]), "+f"(d[1]), "+f"(d[2]), "+f"(d[3]), "+f"(d[4]), "+f"(d[5]), "+f"(d[6]), "+f"(d[7]), "+f"(d[8]), "+f"(d[9]), "+f"(d[10]), "+f"(d[11]), "+f"(d[12]), "+f"(d[13]), "+f"(d[14]), "+f"(d[15]), "+f"(d[16]), "+f"(d[17]), "+f"(d[18]), "+f"(d[19]), "+f"(d[20]), "+f"(d[21]), "+f"(d[22]), "+f"(d[23]), "+f"(d[24]), "+f"(d[25]), "+f"(d[26]), "+f"(d[27]), "+f"(d[28]), "+f"(d[29]), "+f"(d[30]), "+f"(d[31]), "+f"(d[32]), "+f"(d[33]), "+f"(d[34]), "+f"(d[35]), "+f"(d[36]), "+f"(d[37]), "+f"(d[38]), "+f"(d[39]), "+f"(d[40]), "+f"(d[41]), "+f"(d[42]), "+f"(d[43]), "+f"(d[44]), "+f"(d[45]), "+f"(d[46]), "+f"(d[47]), "+f"(d[48]), "+f"(d[49]), "+f"(d[50]), "+f"(d[51]), "+f"(d[52]), "+f"(d[53]), "+f"(d[54]), "+f"(d[55]), "+f"(d[56]), "+f"(d[57]), "+f"(d[58]), "+f"(d[59]), "+f"(d[60]), "+f"(d[61]), "+f"(d[62]), "+f"(d[63]), "+f"(d[64]), "+f"(d[65]), "+f"(d[66]), "+f"(d[67]), "+f"(d[68]), "+f"(d[69]), "+f"(d[70]), "+f"(d[71]), "+f"(d[72]), "+f"(d[73]), "+f"(d[74]), "+f"(d[75]), "+f"(d[76]), "+f"(d[77]), "+f"(d[78]), "+f"(d[79]), "+f"(d[80]), "+f"(d[81]), "+f"(d[82]), "+f"(d[83]), "+f"(d[84]), "+f"(d[85]), "+f"(d[86]), "+f"(d[87]), "+f"(d[88]), "+f"(d[89]), "+f"(d[90]), "+f"(d[91]), "+f"(d[92]), "+f"(d[93]), "+f"(d[94]), "+f"(d[95])
    : "l"(da), "l"(db), "r"(sc));
}

__device__ __forceinline__ void wgmma_ss_n128_tb(float (&d)[64], uint64_t da, uint64_t db, int sc) {
  asm volatile("{\n.reg .pred p;\nsetp.ne.b32 p, %66, 0;\n"
    "wgmma.mma_async.sync.aligned.m64n128k16.f32.bf16.bf16 {%0, %1, %2, %3, %4, %5, %6, %7, %8, %9, %10, %11, %12, %13, %14, %15, %16, %17, %18, %19, %20, %21, %22, %23, %24, %25, %26, %27, %28, %29, %30, %31, %32, %33, %34, %35, %36, %37, %38, %39, %40, %41, %42, %43, %44, %45, %46, %47, %48, %49, %50, %51, %52, %53, %54, %55, %56, %57, %58, %59, %60, %61, %62, %63}, %64, %65, p, 1, 1, 0, 1;\n}\n"
    : "+f"(d[0]), "+f"(d[1]), "+f"(d[2]), "+f"(d[3]), "+f"(d[4]), "+f"(d[5]), "+f"(d[6]), "+f"(d[7]), "+f"(d[8]), "+f"(d[9]), "+f"(d[10]), "+f"(d[11]), "+f"(d[12]), "+f"(d[13]), "+f"(d[14]), "+f"(d[15]), "+f"(d[16]), "+f"(d[17]), "+f"(d[18]), "+f"(d[19]), "+f"(d[20]), "+f"(d[21]), "+f"(d[22]), "+f"(d[23]), "+f"(d[24]), "+f"(d[25]), "+f"(d[26]), "+f"(d[27]), "+f"(d[28]), "+f"(d[29]), "+f"(d[30]), "+f"(d[31]), "+f"(d[32]), "+f"(d[33]), "+f"(d[34]), "+f"(d[35]), "+f"(d[36]), "+f"(d[37]), "+f"(d[38]), "+f"(d[39]), "+f"(d[40]), "+f"(d[41]), "+f"(d[42]), "+f"(d[43]), "+f"(d[44]), "+f"(d[45]), "+f"(d[46]), "+f"(d[47]), "+f"(d[48]), "+f"(d[49]), "+f"(d[50]), "+f"(d[51]), "+f"(d[52]), "+f"(d[53]), "+f"(d[54]), "+f"(d[55]), "+f"(d[56]), "+f"(d[57]), "+f"(d[58]), "+f"(d[59]), "+f"(d[60]), "+f"(d[61]), "+f"(d[62]), "+f"(d[63])
    : "l"(da), "l"(db), "r"(sc));
}

__device__ __forceinline__ void wgmma_ss_n64_tatb(float (&d)[32], uint64_t da, uint64_t db, int sc) {
  asm volatile("{\n.reg .pred p;\nsetp.ne.b32 p, %34, 0;\n"
    "wgmma.mma_async.sync.aligned.m64n64k16.f32.bf16.bf16 {%0, %1, %2, %3, %4, %5, %6, %7, %8, %9, %10, %11, %12, %13, %14, %15, %16, %17, %18, %19, %20, %21, %22, %23, %24, %25, %26, %27, %28, %29, %30, %31}, %32, %33, p, 1, 1, 1, 1;\n}\n"
    : "+f"(d[0]), "+f"(d[1]), "+f"(d[2]), "+f"(d[3]), "+f"(d[4]), "+f"(d[5]), "+f"(d[6]), "+f"(d[7]), "+f"(d[8]), "+f"(d[9]), "+f"(d[10]), "+f"(d[11]), "+f"(d[12]), "+f"(d[13]), "+f"(d[14]), "+f"(d[15]), "+f"(d[16]), "+f"(d[17]), "+f"(d[18]), "+f"(d[19]), "+f"(d[20]), "+f"(d[21]), "+f"(d[22]), "+f"(d[23]), "+f"(d[24]), "+f"(d[25]), "+f"(d[26]), "+f"(d[27]), "+f"(d[28]), "+f"(d[29]), "+f"(d[30]), "+f"(d[31])
    : "l"(da), "l"(db), "r"(sc));
}

__device__ __forceinline__ void wgmma_ss_n8_tatb(float (&d)[4], uint64_t da, uint64_t db, int sc) {
  asm volatile("{\n.reg .pred p;\nsetp.ne.b32 p, %6, 0;\n"
    "wgmma.mma_async.sync.aligned.m64n8k16.f32.bf16.bf16 {%0, %1, %2, %3}, %4, %5, p, 1, 1, 1, 1;\n}\n"
    : "+f"(d[0]), "+f"(d[1]), "+f"(d[2]), "+f"(d[3])
    : "l"(da), "l"(db), "r"(sc));
}

__device__ __forceinline__ void wgmma_rs_n40_tb(float (&d)[20], uint32_t a0, uint32_t a1, uint32_t a2, uint32_t a3, uint64_t db, int sc) {
  asm volatile("{\n.reg .pred p;\nsetp.ne.b32 p, %25, 0;\n"
    "wgmma.mma_async.sync.aligned.m64n40k16.f32.bf16.bf16 {%0, %1, %2, %3, %4, %5, %6, %7, %8, %9, %10, %11, %12, %13, %14, %15, %16, %17, %18, %19}, {%20, %21, %22, %23}, %24, p, 1, 1, 1;\n}\n"
    : "+f"(d[0]), "+f"(d[1]), "+f"(d[2]), "+f"(d[3]), "+f"(d[4]), "+f"(d[5]), "+f"(d[6]), "+f"(d[7]), "+f"(d[8]), "+f"(d[9]), "+f"(d[10]), "+f"(d[11]), "+f"(d[12]), "+f"(d[13]), "+f"(d[14]), "+f"(d[15]), "+f"(d[16]), "+f"(d[17]), "+f"(d[18]), "+f"(d[19])
    : "r"(a0), "r"(a1), "r"(a2), "r"(a3), "l"(db), "r"(sc));
}

namespace k1 {
constexpr int BM = 256, BN = 192, BK = 64, ST = 4;
constexpr int A_BYTES = BM * BK * 2, B_BYTES = BK * BN * 2, STAGE = A_BYTES + B_BYTES;
constexpr int SMEM = ST * STAGE + 1024 + 256;
constexpr int OFF_PK = 0, OFF_V = 32768, OFF_ONES = 65536, OFF_KV = 69632, OFF_O = 81920, OFF_RED = 114688;
}

__global__ void __cluster_dims__(2, 1, 1) __launch_bounds__(384, 1)
k1_qkv_attn(const __grid_constant__ CUtensorMap tmx, const __grid_constant__ CUtensorMap tmw) {
  using namespace k1;
  extern __shared__ uint8_t smem_raw[];
  const uint32_t sbase = (smem_u32(smem_raw) + 1023) & ~1023u;
  uint8_t* sgen = smem_raw + (sbase - smem_u32(smem_raw));
  const uint32_t bars = sbase + ST * STAGE;
  const int tid = threadIdx.x, warp = tid >> 5, lane = tid & 31;
  const uint32_t rank = cluster_ctarank();
  const int cl = blockIdx.x >> 1;
  const int mt = cl >> 3;
  const int hp = ((cl & 7) << 1) + rank;
  const int m0 = mt * BM;

  if (tid == 0) {
    for (int s = 0; s < ST; s++) {
      mbar_init(bars + 8 * s, 1);
      mbar_init(bars + 8 * (ST + s), 16);
    }
    asm volatile("fence.mbarrier_init.release.cluster;" ::: "memory");
  }
  cluster_sync_all();
  pdl_launch();

  if (warp >= 8) {
    asm volatile("setmaxnreg.dec.sync.aligned.u32 40;");
    if (warp == 8 && lane == 0) {
      for (int kb = 0; kb < DM / BK; kb++) {
        const int s = kb % ST;
        mbar_wait(bars + 8 * (ST + s), ((kb / ST) & 1) ^ 1);
        const uint32_t full = bars + 8 * s;
        mbar_expect_tx(full, STAGE);
        const uint32_t sa = sbase + s * STAGE, sb = sa + A_BYTES;
        tma_load_2d_mc(sa + rank * 16384, &tmx, full, kb * BK, m0 + rank * 128, (uint16_t)3);
#pragma unroll
        for (int j = 0; j < 3; j++) tma_load_2d(sb + j * 8192, &tmw, full, j * 1024 + hp * 64, kb * BK);
      }
      pdl_wait();
    }
    cluster_sync_all();
  } else {
    asm volatile("setmaxnreg.inc.sync.aligned.u32 232;");
    const int wg = warp >> 2, w4 = warp & 3, g = lane >> 2, t = lane & 3;
    if (tid == 0) TS(1, 0);
    float acc[2][96];
#pragma unroll
    for (int i = 0; i < 96; i++) { acc[0][i] = 0.f; acc[1][i] = 0.f; }
    for (int kb = 0; kb < DM / BK; kb++) {
      const int s = kb % ST;
      mbar_wait(bars + 8 * s, (kb / ST) & 1);
      const uint32_t sa = sbase + s * STAGE + wg * 16384, sb = sbase + s * STAGE + A_BYTES;
      wg_fence();
#pragma unroll
      for (int ks = 0; ks < 4; ks++) {
        const uint64_t db = make_desc(sb + ks * 2048, 8192, 1024);
#pragma unroll
        for (int mb = 0; mb < 2; mb++) {
          const uint64_t da = make_desc(sa + mb * 8192 + ks * 32, 16, 1024);
          wgmma_ss_n192_tb(acc[mb], da, db, 1);
        }
      }
      wg_commit();
      if (kb > 0) {
        wg_wait<1>();
        const int sp = (kb - 1) % ST;
        if (lane == 0) { mbar_arrive_cluster(bars + 8 * (ST + sp), 0); mbar_arrive_cluster(bars + 8 * (ST + sp), 1); }
      }
    }
    wg_wait<0>();
    fence_regs(acc[0]); fence_regs(acc[1]);
    if (tid == 0) TS(1, 1);
    named_bar_sync(1, 256);

#pragma unroll
    for (int mb = 0; mb < 2; mb++) {
#pragma unroll
      for (int h = 0; h < 2; h++) {
        const int r = wg * 128 + mb * 64 + w4 * 16 + g + h * 8;
#pragma unroll
        for (int j = 0; j < 8; j++) {
          const uint32_t off = r * 128 + ((j ^ (r & 7)) << 4) + t * 4;
          const float k0 = acc[mb][4 * (8 + j) + 2 * h], k1v = acc[mb][4 * (8 + j) + 2 * h + 1];
          const float v0 = acc[mb][4 * (16 + j) + 2 * h], v1 = acc[mb][4 * (16 + j) + 2 * h + 1];
          *reinterpret_cast<uint32_t*>(sgen + OFF_PK + off) = phi2(k0, k1v);
          *reinterpret_cast<uint32_t*>(sgen + OFF_V + off) = pack2(v0, v1);
        }
      }
    }
    if (tid < 256) *reinterpret_cast<uint32_t*>(sgen + OFF_ONES + tid * 4) = 0x3F803F80u;
    fence_async_smem();
    named_bar_sync(1, 256);

    if (tid == 0) TS(1, 2);
    float* part = g_part + (size_t)(hp * 8 + mt) * 2112;
    {
      float kv[32], zz[4];
#pragma unroll
      for (int i = 0; i < 32; i++) kv[i] = 0.f;
#pragma unroll
      for (int i = 0; i < 4; i++) zz[i] = 0.f;
      wg_fence();
#pragma unroll
      for (int ks = 0; ks < 8; ks++) {
        const uint64_t da = make_desc(sbase + OFF_PK + wg * 16384 + ks * 2048, 16, 1024);
        const uint64_t db = make_desc(sbase + OFF_V + wg * 16384 + ks * 2048, 16, 1024);
        const uint64_t d1 = make_desc(sbase + OFF_ONES, 16, 0);
        wgmma_ss_n64_tatb(kv, da, db, 1);
        wgmma_ss_n8_tatb(zz, da, d1, 1);
      }
      wg_commit();
      wg_wait<0>();
      fence_regs(kv); fence_regs(zz);
      const int hh = w4 >> 1;
      float* red = reinterpret_cast<float*>(sgen + OFF_RED);
      float vals[2][4][2];
#pragma unroll
      for (int h = 0; h < 2; h++)
#pragma unroll
        for (int j = 0; j < 4; j++) {
          vals[h][j][0] = hh ? kv[4 * (4 + j) + 2 * h] : kv[4 * j + 2 * h];
          vals[h][j][1] = hh ? kv[4 * (4 + j) + 2 * h + 1] : kv[4 * j + 2 * h + 1];
        }
      if (wg == 1) {
#pragma unroll
        for (int h = 0; h < 2; h++) {
          const int d = (w4 & 1) * 16 + g + h * 8;
#pragma unroll
          for (int j = 0; j < 4; j++)
            *reinterpret_cast<float2*>(red + hh * 1056 + d * 32 + 8 * j + 2 * t) = make_float2(vals[h][j][0], vals[h][j][1]);
          if (t == 0) red[hh * 1056 + 1024 + d] = zz[2 * h];
        }
      }
      named_bar_sync(1, 256);
      if (wg == 0) {
#pragma unroll
        for (int h = 0; h < 2; h++) {
          const int d = (w4 & 1) * 16 + g + h * 8;
#pragma unroll
          for (int j = 0; j < 4; j++) {
            const float2 o = *reinterpret_cast<const float2*>(red + hh * 1056 + d * 32 + 8 * j + 2 * t);
            *reinterpret_cast<float2*>(part + hh * 1056 + d * 32 + 8 * j + 2 * t) = make_float2(vals[h][j][0] + o.x, vals[h][j][1] + o.y);
          }
          if (t == 0) part[hh * 1056 + 1024 + d] = zz[2 * h] + red[hh * 1056 + 1024 + d];
        }
        __threadfence();
        named_bar_sync(2, 128);
        if (tid == 0) atomicAdd(&g_cnt[hp], 1u);
      }
    }
    if (tid == 0) TS(1, 3);
    uint32_t pq[2][4][4];
#pragma unroll
    for (int mb = 0; mb < 2; mb++)
#pragma unroll
      for (int kk = 0; kk < 4; kk++) {
        pq[mb][kk][0] = phi2(acc[mb][8 * kk + 0], acc[mb][8 * kk + 1]);
        pq[mb][kk][1] = phi2(acc[mb][8 * kk + 2], acc[mb][8 * kk + 3]);
        pq[mb][kk][2] = phi2(acc[mb][8 * kk + 4], acc[mb][8 * kk + 5]);
        pq[mb][kk][3] = phi2(acc[mb][8 * kk + 6], acc[mb][8 * kk + 7]);
      }
    if (tid == 0) TS(1, 4);
    if (tid == 0) {
      unsigned int v;
      do { asm volatile("ld.acquire.gpu.global.u32 %0, [%1];" : "=r"(v) : "l"(&g_cnt[hp]) : "memory"); } while (v < 8u);
    }
    named_bar_sync(1, 256);
    {
      if (tid == 0) TS(1, 5);
      const float* pb = g_part + (size_t)(hp * 8) * 2112;
      for (int i = tid; i < 528; i += 256) {
        float4 s4 = make_float4(0.f, 0.f, 0.f, 0.f);
#pragma unroll
        for (int p = 0; p < 8; p++) {
          float4 v4 = __ldcg(reinterpret_cast<const float4*>(pb + p * 2112) + i);
          s4.x += v4.x; s4.y += v4.y; s4.z += v4.z; s4.w += v4.w;
        }
        const int hh = i / 264, rem = i - hh * 264;
        uint8_t* tile = sgen + OFF_KV + hh * 4096;
        if (rem < 256) {
          const int d = rem >> 3, e = (rem & 7) * 4;
          const uint32_t off = d * 128 + (((e >> 3) ^ (d & 7)) << 4) + (e & 7) * 2;
          *reinterpret_cast<uint2*>(tile + off) = make_uint2(pack2(s4.x, s4.y), pack2(s4.z, s4.w));
        } else {
          const int d0 = (rem - 256) * 4;
          float zv[4] = {s4.x, s4.y, s4.z, s4.w};
#pragma unroll
          for (int q = 0; q < 4; q++) {
            const int d = d0 + q;
            const uint32_t off = d * 128 + ((4 ^ (d & 7)) << 4);
            *reinterpret_cast<uint4*>(tile + off) = make_uint4(pack2(zv[q], 0.f), 0u, 0u, 0u);
          }
        }
      }
    }
    fence_async_smem();
    named_bar_sync(1, 256);
    if (tid == 0) TS(1, 6);
#pragma unroll
    for (int mb = 0; mb < 2; mb++) {
#pragma unroll
      for (int hh = 0; hh < 2; hh++) {
        float num[20];
#pragma unroll
        for (int i = 0; i < 20; i++) num[i] = 0.f;
        wg_fence();
#pragma unroll
        for (int kk = 0; kk < 2; kk++) {
          const uint64_t db = make_desc(sbase + OFF_KV + hh * 4096 + kk * 2048, 16, 1024);
          wgmma_rs_n40_tb(num, pq[mb][hh * 2 + kk][0], pq[mb][hh * 2 + kk][1], pq[mb][hh * 2 + kk][2], pq[mb][hh * 2 + kk][3], db, 1);
        }
        wg_commit();
        wg_wait<0>();
        fence_regs(num);
#pragma unroll
        for (int h = 0; h < 2; h++) {
          float den = __shfl_sync(0xffffffffu, num[16 + 2 * h], lane & ~3);
          den = bfr(bfr(den) + 1e-6f);
          const float rden = 1.0f / den;
          const int r = wg * 128 + mb * 64 + w4 * 16 + g + h * 8;
#pragma unroll
          for (int j = 0; j < 4; j++) {
            const uint32_t n2 = pack2(num[4 * j + 2 * h], num[4 * j + 2 * h + 1]);
            const float o0 = lo_f(n2) * rden, o1 = hi_f(n2) * rden;
            const uint32_t off = r * 128 + (((hh * 4 + j) ^ (r & 7)) << 4) + t * 4;
            *reinterpret_cast<uint32_t*>(sgen + OFF_O + off) = pack2(o0, o1);
          }
        }
      }
    }
    named_bar_sync(1, 256);
    if (tid == 0) TS(1, 7);
    for (int i = tid; i < 256 * 8; i += 256) {
      const int r = i >> 3, c = i & 7;
      uint4 v = *reinterpret_cast<const uint4*>(sgen + OFF_O + r * 128 + ((c ^ (r & 7)) << 4));
      *reinterpret_cast<uint4*>(g_o + (size_t)(m0 + r) * DM + hp * 64 + c * 8) = v;
    }
    if (tid == 0) TS(1, 8);
    cluster_sync_all();
  }
}

namespace k3 {
constexpr int BM = 128, BN = 128, BK = 64, ST = 5;
constexpr int A_BYTES = BM * BK * 2, B_BYTES = BK * BN * 2, STAGE = A_BYTES + B_BYTES;
constexpr int OFF_BT = ST * STAGE;
constexpr int OFF_BAR = OFF_BT + 32768;
constexpr int SMEM = OFF_BAR + 1024 + 256;
}

__global__ void __cluster_dims__(2, 1, 1) __launch_bounds__(384, 1)
k3_out(const __grid_constant__ CUtensorMap tmo, const __grid_constant__ CUtensorMap tmw,
       const __grid_constant__ CUtensorMap tmbt, const __grid_constant__ CUtensorMap tmout) {
  using namespace k3;
  extern __shared__ uint8_t smem_raw[];
  const uint32_t sbase = (smem_u32(smem_raw) + 1023) & ~1023u;
  uint8_t* sgen = smem_raw + (sbase - smem_u32(smem_raw));
  const uint32_t bars = sbase + OFF_BAR;
  const uint32_t barbt = bars + 8 * 2 * ST;
  const int tid = threadIdx.x, warp = tid >> 5, lane = tid & 31;
  const uint32_t rank = cluster_ctarank();
  const int cl = blockIdx.x >> 1;
  const int mt = cl >> 2;
  const int nt = ((cl & 3) << 1) + rank;
  const int m0 = mt * BM, n0 = nt * BN;

  if (tid == 0) {
    for (int s = 0; s < ST; s++) {
      mbar_init(bars + 8 * s, 1);
      mbar_init(bars + 8 * (ST + s), 16);
    }
    mbar_init(barbt, 1);
    asm volatile("fence.mbarrier_init.release.cluster;" ::: "memory");
  }
  cluster_sync_all();

  if (warp >= 8) {
    asm volatile("setmaxnreg.dec.sync.aligned.u32 40;");
    if (warp == 8 && lane == 0) {
      for (int kb = 0; kb < ST; kb++) {
        const uint32_t full = bars + 8 * kb;
        mbar_expect_tx(full, STAGE);
        const uint32_t sb = sbase + kb * STAGE + A_BYTES;
#pragma unroll
        for (int j = 0; j < 2; j++) tma_load_2d(sb + j * 8192, &tmw, full, n0 + j * 64, kb * BK);
      }
      pdl_wait();
      if (blockIdx.x == 0) for (int i = 0; i < 16; i++) g_cnt[i] = 0;
      for (int kb = 0; kb < DM / BK; kb++) {
        const int s = kb % ST;
        const uint32_t full = bars + 8 * s;
        const uint32_t sa = sbase + s * STAGE, sb = sa + A_BYTES;
        if (kb >= ST) {
          mbar_wait(bars + 8 * (ST + s), ((kb / ST) & 1) ^ 1);
          mbar_expect_tx(full, STAGE);
#pragma unroll
          for (int j = 0; j < 2; j++) tma_load_2d(sb + j * 8192, &tmw, full, n0 + j * 64, kb * BK);
        }
        tma_load_2d_mc(sa + rank * 8192, &tmo, full, kb * BK, m0 + rank * 64, (uint16_t)3);
        if (kb == 2) {
          mbar_expect_tx(barbt, 32768);
          tma_load_2d(sbase + OFF_BT, &tmbt, barbt, m0, n0);
          tma_load_2d(sbase + OFF_BT + 16384, &tmbt, barbt, m0 + 64, n0);
        }
      }
    }
    cluster_sync_all();
  } else {
    asm volatile("setmaxnreg.inc.sync.aligned.u32 232;");
    const int wg = warp >> 2, w4 = warp & 3, g = lane >> 2, t = lane & 3;
    if (tid == 0) TS(3, 0);
    float acc[64];
#pragma unroll
    for (int i = 0; i < 64; i++) acc[i] = 0.f;
    for (int kb = 0; kb < DM / BK; kb++) {
      const int s = kb % ST;
      mbar_wait(bars + 8 * s, (kb / ST) & 1);
      const uint32_t sa = sbase + s * STAGE + wg * 8192, sb = sbase + s * STAGE + A_BYTES;
      wg_fence();
#pragma unroll
      for (int ks = 0; ks < 4; ks++) {
        const uint64_t db = make_desc(sb + ks * 2048, 8192, 1024);
        const uint64_t da = make_desc(sa + ks * 32, 16, 1024);
        wgmma_ss_n128_tb(acc, da, db, 1);
      }
      wg_commit();
      if (kb > 0) {
        wg_wait<1>();
        const int sp = (kb - 1) % ST;
        if (lane == 0) { mbar_arrive_cluster(bars + 8 * (ST + sp), 0); mbar_arrive_cluster(bars + 8 * (ST + sp), 1); }
      }
    }
    wg_wait<0>();
    fence_regs(acc);
    if (tid == 0) TS(3, 1);
    named_bar_sync(1, 256);
    mbar_wait(barbt, 0);
    pdl_wait();
#pragma unroll
    for (int h = 0; h < 2; h++) {
      const int rl = wg * 64 + w4 * 16 + g + h * 8;
      const float gt = g_gate[m0 + rl];
      const float omg = bfr(1.0f - gt);
      const uint8_t* bt = sgen + OFF_BT + wg * 16384;
      const int ll = rl & 63;
#pragma unroll
      for (int j = 0; j < 16; j++) {
        const int c = 8 * j + 2 * t;
        const float b0 = __bfloat162float(*reinterpret_cast<const bf16*>(bt + c * 128 + (((ll >> 3) ^ (c & 7)) << 4) + (ll & 7) * 2));
        const float b1 = __bfloat162float(*reinterpret_cast<const bf16*>(bt + (c + 1) * 128 + (((ll >> 3) ^ ((c + 1) & 7)) << 4) + (ll & 7) * 2));
        const uint32_t a2 = pack2(acc[4 * j + 2 * h], acc[4 * j + 2 * h + 1]);
        const float o0 = bfr(gt * lo_f(a2)) + bfr(omg * b0);
        const float o1 = bfr(gt * hi_f(a2)) + bfr(omg * b1);
        *reinterpret_cast<uint32_t*>(sgen + (j >> 3) * 16384 + rl * 128 + (((j & 7) ^ (rl & 7)) << 4) + t * 4) = pack2(o0, o1);
      }
    }
    fence_async_smem();
    if (tid == 0) TS(3, 2);
    named_bar_sync(2 + wg, 128);
    if ((tid & 127) == 0) {
#pragma unroll
      for (int j = 0; j < 2; j++)
        asm volatile("cp.async.bulk.tensor.2d.global.shared::cta.bulk_group [%0, {%2, %3}], [%1];" ::"l"(&tmout),
                     "r"(sbase + j * 16384 + wg * 8192), "r"(n0 + j * 64), "r"(m0 + wg * 64) : "memory");
      asm volatile("cp.async.bulk.commit_group;" ::: "memory");
      asm volatile("cp.async.bulk.wait_group.read 0;" ::: "memory");
      if (tid == 0) TS(3, 3);
    }
    cluster_sync_all();
  }
}

__device__ __align__(1024) bf16 g_bT[DM * SEQ];
constexpr int KOFF = 2048 + 16;
constexpr int KSZ = 2112;
constexpr int KCH = 2 * KSZ + 16;

__device__ __forceinline__ void mma_bf16(float (&d)[4], uint32_t a0, uint32_t a1, uint32_t a2, uint32_t a3, uint32_t b0, uint32_t b1) {
  asm volatile("mma.sync.aligned.m16n8k16.row.col.f32.bf16.bf16.f32 {%0,%1,%2,%3}, {%4,%5,%6,%7}, {%8,%9}, {%0,%1,%2,%3};"
               : "+f"(d[0]), "+f"(d[1]), "+f"(d[2]), "+f"(d[3]) : "r"(a0), "r"(a1), "r"(a2), "r"(a3), "r"(b0), "r"(b1));
}
__device__ __forceinline__ void mma_f16(float (&d)[4], uint32_t a0, uint32_t a1, uint32_t a2, uint32_t a3, uint32_t b0, uint32_t b1) {
  asm volatile("mma.sync.aligned.m16n8k16.row.col.f32.f16.f16.f32 {%0,%1,%2,%3}, {%4,%5,%6,%7}, {%8,%9}, {%0,%1,%2,%3};"
               : "+f"(d[0]), "+f"(d[1]), "+f"(d[2]), "+f"(d[3]) : "r"(a0), "r"(a1), "r"(a2), "r"(a3), "r"(b0), "r"(b1));
}
struct cf { float r, i; };
__device__ __forceinline__ cf cmul(cf a, cf b) { cf c; c.r = a.r * b.r - a.i * b.i; c.i = a.r * b.i + a.i * b.r; return c; }
__device__ __forceinline__ cf csq(cf a) { cf c; c.r = a.r * a.r - a.i * a.i; c.i = 2.f * a.r * a.i; return c; }
__device__ __forceinline__ cf cexpp(float ar, float ai, float p) {
  const float e = ex2f(ar * p * 1.4426950408889634f);
  const float th = ai * p;
  const float k = rintf(th * 0.15915494309189535f);
  float r = fmaf(k, -6.2831854820251465f, th);
  r = fmaf(k, 1.7484556000744e-7f, r);
  cf w; w.r = e * __cosf(r); w.i = e * __sinf(r); return w;
}
__device__ __forceinline__ uint32_t packh(float lo, float hi) {
  uint32_t r; asm("cvt.rn.f16x2.f32 %0, %1, %2;" : "=r"(r) : "f"(hi), "f"(lo)); return r;
}

namespace k2 {
constexpr int CH = 8;
constexpr int USEG = 272;
constexpr int USZ = USEG * 9 + 16;
constexpr int TSTR = 40;
constexpr int TABW = 72 * TSTR;
constexpr int P_TAP0 = 0, P_TAPS = 304, P_V2 = 976, P_V4 = 3088, P_V8 = 4752, PAIRW = 6032;
constexpr int OFF_U = 0;
constexpr int OFF_P = OFF_U + CH * USZ * 2;
constexpr int SMEM = OFF_P + CH * PAIRW * 4;
}

__global__ void __launch_bounds__(512, 1)
k2_ssm(const bf16* __restrict__ x, const bf16* __restrict__ logAr, const bf16* __restrict__ Aim, const bf16* __restrict__ Cre,
       const bf16* __restrict__ Cim, const bf16* __restrict__ logdt, const bf16* __restrict__ Dskip,
       const bf16* __restrict__ gatew) {
  using namespace k2;
  extern __shared__ __align__(16) uint8_t sm[];
  const int tid = threadIdx.x, warp = tid >> 5, lane = tid & 31, g = lane >> 2, t = lane & 3;
  const int ch = warp >> 1, half = warp & 1, l64 = half * 32 + lane;
  const int d0 = blockIdx.x * CH;
  bf16* us = reinterpret_cast<bf16*>(sm + OFF_U);
  uint32_t* pw = reinterpret_cast<uint32_t*>(sm + OFF_P) + ch * PAIRW;
  if (tid == 0) TS(2, 0);
  pdl_launch();

  uint4 uv[2][2];
#pragma unroll
  for (int it = 0; it < 2; it++) {
    const int l = 2 * (tid + it * 512);
    uv[it][0] = __ldg(reinterpret_cast<const uint4*>(x + (size_t)l * DM + d0));
    uv[it][1] = __ldg(reinterpret_cast<const uint4*>(x + (size_t)(l + 1) * DM + d0));
  }
  const int d = d0 + ch;
  bf16 p_la[2], p_ai[2], p_cr[2], p_ci[2];
#pragma unroll
  for (int c = 0; c < 2; c++) {
    const int idx = d * NMODE + half * 64 + c * 32 + lane;
    p_la[c] = logAr[idx]; p_ai[c] = Aim[idx]; p_cr[c] = Cre[idx]; p_ci[c] = Cim[idx];
  }
  const bf16 p_dt = logdt[d];
  {
    const int r = blockIdx.x * 16 + warp;
    float s = 0.f;
#pragma unroll
    for (int c = lane * 8; c < DM; c += 256) {
      const uint4 xv = __ldg(reinterpret_cast<const uint4*>(x + (size_t)r * DM + c));
      const uint4 wv = __ldg(reinterpret_cast<const uint4*>(gatew + c));
      const bf16* xp = reinterpret_cast<const bf16*>(&xv);
      const bf16* wp = reinterpret_cast<const bf16*>(&wv);
#pragma unroll
      for (int q = 0; q < 8; q++) s += bfr(__bfloat162float(xp[q]) * __bfloat162float(wp[q]));
    }
#pragma unroll
    for (int o = 16; o; o >>= 1) s += __shfl_xor_sync(0xffffffffu, s, o);
    if (lane == 0) { const float z = bfr(s); g_gate[r] = bfr(1.0f / (1.0f + ex2f(-z * 1.4426950408889634f))); }
  }
  for (int i = tid; i < CH * (USEG / 2 + 8); i += 512) {
    const int c = i / (USEG / 2 + 8), o = i % (USEG / 2 + 8);
    reinterpret_cast<uint32_t*>(us + c * USZ)[o < USEG / 2 ? o : (USEG * 9) / 2 + (o - USEG / 2)] = 0u;
  }
#pragma unroll
  for (int it = 0; it < 2; it++) {
    const int l = 2 * (tid + it * 512);
    const int e = l & 15;
    const int pe = ((e & 7) >> 1) * 4 + (e >> 3) * 2;
    const int pos = USEG * (1 + (l >> 8)) + (l & 240) + pe;
    const uint32_t a[4] = {uv[it][0].x, uv[it][0].y, uv[it][0].z, uv[it][0].w};
    const uint32_t b[4] = {uv[it][1].x, uv[it][1].y, uv[it][1].z, uv[it][1].w};
#pragma unroll
    for (int c = 0; c < 4; c++) {
      *reinterpret_cast<uint32_t*>(us + (2 * c) * USZ + pos) = __byte_perm(a[c], b[c], 0x5410);
      *reinterpret_cast<uint32_t*>(us + (2 * c + 1) * USZ + pos) = __byte_perm(a[c], b[c], 0x7632);
    }
  }

  float acc[5][4];
#pragma unroll
  for (int a = 0; a < 5; a++)
#pragma unroll
    for (int b = 0; b < 4; b++) acc[a][b] = 0.f;
  float last = 0.f, scale;
  {
    const float dt = bfr(ex2f(__bfloat162float(p_dt) * 1.4426950408889634f));
    float cr[2], ci[2], arr[2], aii[2];
#pragma unroll
    for (int c = 0; c < 2; c++) {
      arr[c] = -bfr(ex2f(__bfloat162float(p_la[c]) * 1.4426950408889634f)) * dt;
      aii[c] = __bfloat162float(p_ai[c]) * dt;
      cr[c] = __bfloat162float(p_cr[c]) * dt;
      ci[c] = __bfloat162float(p_ci[c]) * dt;
    }
    float mx = fmaxf(fmaxf(fabsf(cr[0]), fabsf(ci[0])), fmaxf(fabsf(cr[1]), fabsf(ci[1])));
#pragma unroll
    for (int o = 16; o; o >>= 1) mx = fmaxf(mx, __shfl_xor_sync(0xffffffffu, mx, o));
    {
      int e = (int)((__float_as_uint(mx) >> 23) & 255u) + 1;
      e = e < 32 ? 32 : (e > 220 ? 220 : e);
      scale = __uint_as_float((uint32_t)e << 23);
    }
    const float iscale = __uint_as_float((uint32_t)(254 - ((__float_as_uint(scale) >> 23) & 255u)) << 23);
    uint32_t* tab = pw + half * TABW;
#pragma unroll 1
    for (int c = 0; c < 2; c++) {
      const float ar = arr[c], ai = aii[c];
      cf C; C.r = cr[c] * iscale; C.i = ci[c] * iscale;
      const cf W1 = cexpp(ar, ai, 1.f), W16 = cexpp(ar, ai, 16.f), W256 = cexpp(ar, ai, 256.f);
      const cf W512 = csq(W256), W1024 = csq(W512);
      const cf W1536 = cmul(W1024, W512);
      {
        const cf w2048 = csq(W1024);
        last += cr[c] * w2048.r - ci[c] * w2048.i;
      }
      uint32_t* tp = tab + lane;
      {
        cf xa = C;
#pragma unroll
        for (int i = 0; i < 16; i++) {
          tp[i * TSTR] = packh(xa.r, -xa.i);
          if ((i & 1) == 0) {
            tp[(16 + i / 2) * TSTR] = packh(xa.r, -xa.i);
            const cf xb = cmul(xa, W256);
            tp[(24 + i / 2) * TSTR] = packh(xb.r, -xb.i);
          }
          xa = cmul(xa, W16);
        }
      }
      {
        cf y; y.r = 1.f; y.i = 0.f;
        const cf W528 = cmul(W512, W16);
        const cf WA16 = cmul(W1024, W16), WB16 = cmul(W1536, W16);
#pragma unroll
        for (int j = 0; j < 16; j++) {
          tp[(32 + j) * TSTR] = packh(y.r, y.i);
          if ((j & 1) == 0) { const cf z = cmul(y, W256); tp[(48 + j / 2) * TSTR] = packh(z.r, z.i); }
          if ((j & 3) == 0) {
            const cf z0 = cmul(y, W512), z1 = cmul(y, W528);
            tp[(56 + j / 4) * TSTR] = packh(z0.r, z0.i);
            tp[(60 + j / 4) * TSTR] = packh(z1.r, z1.i);
          }
          if ((j & 7) == 0) {
            const cf z0 = cmul(y, W1024), z1 = cmul(y, WA16), z2 = cmul(y, W1536), z3 = cmul(y, WB16);
            tp[(64 + j / 8) * TSTR] = packh(z0.r, z0.i);
            tp[(66 + j / 8) * TSTR] = packh(z1.r, z1.i);
            tp[(68 + j / 8) * TSTR] = packh(z2.r, z2.i);
            tp[(70 + j / 8) * TSTR] = packh(z3.r, z3.i);
          }
          y = cmul(y, W1);
        }
      }
      __syncwarp();
#pragma unroll
      for (int ks4 = 0; ks4 < 4; ks4++) {
        const uint32_t* fp = tab + 8 * ks4 + 2 * t;
        const uint2 xa0 = *reinterpret_cast<const uint2*>(fp + g * TSTR), xa1 = *reinterpret_cast<const uint2*>(fp + (g + 8) * TSTR);
        const uint2 xb0 = *reinterpret_cast<const uint2*>(fp + (16 + g) * TSTR), xb1 = *reinterpret_cast<const uint2*>(fp + (24 + g) * TSTR);
        const uint2 y1 = *reinterpret_cast<const uint2*>(fp + (32 + g) * TSTR), y2 = *reinterpret_cast<const uint2*>(fp + (40 + g) * TSTR);
        const uint2 y3 = *reinterpret_cast<const uint2*>(fp + (48 + g) * TSTR), y4 = *reinterpret_cast<const uint2*>(fp + (56 + g) * TSTR);
        const uint2 y5 = *reinterpret_cast<const uint2*>(fp + (64 + g) * TSTR);
        mma_f16(acc[0], xa0.x, xa1.x, xa0.y, xa1.y, y1.x, y1.y);
        mma_f16(acc[1], xa0.x, xa1.x, xa0.y, xa1.y, y2.x, y2.y);
        mma_f16(acc[2], xa0.x, xa1.x, xa0.y, xa1.y, y3.x, y3.y);
        mma_f16(acc[3], xb0.x, xb1.x, xb0.y, xb1.y, y4.x, y4.y);
        mma_f16(acc[4], xb0.x, xb1.x, xb0.y, xb1.y, y5.x, y5.y);
      }
      __syncwarp();
    }
  }
  if (tid == 0) TS(2, 1);
  __syncthreads();
  float* kqp = reinterpret_cast<float*>(pw + P_V2);
  {
    float* kq = kqp + half * 648;
    const float sc2 = 2.f * scale;
#pragma unroll
    for (int h = 0; h < 2; h++) {
      const int i = g + 8 * h;
      *reinterpret_cast<float2*>(kq + 16 * i + 2 * t) = make_float2(sc2 * acc[0][2 * h], sc2 * acc[0][2 * h + 1]);
      *reinterpret_cast<float2*>(kq + 16 * i + 8 + 2 * t) = make_float2(sc2 * acc[1][2 * h], sc2 * acc[1][2 * h + 1]);
      *reinterpret_cast<float2*>(kq + 256 + 8 * i + 2 * t) = make_float2(sc2 * acc[2][2 * h], sc2 * acc[2][2 * h + 1]);
      *reinterpret_cast<float2*>(kq + 384 + 8 * i + 2 * t) = make_float2(sc2 * acc[3][2 * h], sc2 * acc[3][2 * h + 1]);
      *reinterpret_cast<float2*>(kq + 512 + 4 * i + 64 * (t >> 1) + 2 * (t & 1)) = make_float2(sc2 * acc[4][2 * h], sc2 * acc[4][2 * h + 1]);
    }
#pragma unroll
    for (int o = 16; o; o >>= 1) last += __shfl_xor_sync(0xffffffffu, last, o);
    if (lane == 0) kq[640] = 2.f * last;
  }
  named_bar_sync(1 + ch, 64);
  float k1024b;
  {
    auto KQ = [&](int id) { return kqp[id] + kqp[648 + id]; };
    for (int w = l64; w < 144; w += 64) {
      float v[3];
#pragma unroll
      for (int q = 0; q < 3; q++) {
        const int xx = 272 - 2 * w - q;
        float val = 0.f;
        if (xx >= 0 && xx < 256) { val = KQ(xx); if (xx == 255) val -= bfr(KQ(256)); }
        v[q] = val;
      }
      pw[P_TAP0 + w] = pack2(v[0], v[1]);
      pw[P_TAP0 + 152 + w] = pack2(v[1], v[2]);
    }
    for (int i = l64; i < 6 * 50; i += 64) {
      const int a = i / 50, w = i - a * 50;
      const int base = 128 + (a >> 1) * 128 + (a & 1);
      float v[3];
#pragma unroll
      for (int q = 0; q < 3; q++) {
        const int xx = 144 - 2 * w - q;
        float val = 0.f;
        if (xx >= 64 && (xx < 128 || (xx == 128 && a == 4))) {
          val = KQ(base + 2 * xx);
          if (a == 1 && xx == 127) val -= bfr(KQ(384));
        }
        v[q] = val;
      }
      pw[P_TAPS + a * 112 + w] = pack2(v[0], v[1]);
      pw[P_TAPS + a * 112 + 56 + w] = pack2(v[1], v[2]);
    }
    k1024b = bfr(KQ(512));
  }
  named_bar_sync(1 + ch, 64);
  for (int i = l64; i < (PAIRW - P_V2) / 4; i += 64) *reinterpret_cast<uint4*>(pw + P_V2 + 4 * i) = make_uint4(0u, 0u, 0u, 0u);
  named_bar_sync(1 + ch, 64);
  const bf16* uc = us + ch * USZ;
  if (l64 < 56 || l64 == 63) {
    const int t0 = l64 == 63 ? -32 : 32 * l64;
    float P[65];
    P[0] = 0.f;
#pragma unroll
    for (int gi = 0; gi < 4; gi++) {
      const int tg = t0 - 16 + 16 * gi;
      const int ad = tg < 0 ? (tg & 240) : USEG * (1 + (tg >> 8)) + (tg & 240);
      const uint4 v0 = *reinterpret_cast<const uint4*>(uc + ad), v1 = *reinterpret_cast<const uint4*>(uc + ad + 8);
      const uint32_t w[8] = {v0.x, v0.y, v0.z, v0.w, v1.x, v1.y, v1.z, v1.w};
      float e[16];
#pragma unroll
      for (int q = 0; q < 4; q++) {
        e[2 * q] = lo_f(w[2 * q]); e[2 * q + 1] = hi_f(w[2 * q]);
        e[2 * q + 8] = lo_f(w[2 * q + 1]); e[2 * q + 9] = hi_f(w[2 * q + 1]);
      }
#pragma unroll
      for (int q = 0; q < 16; q++) P[16 * gi + q + 1] = P[16 * gi + q] + e[q];
    }
#define WIN(j, lo, hi) (P[17 + (j) + (hi)] - P[16 + (j) + (lo)])
    {
      const int qq0 = (t0 >> 2) + 32;
      uint32_t* b2 = pw + P_V2 + (qq0 & ~15) / 2 + ((qq0 >> 3) & 1);
#pragma unroll
      for (int rho = 0; rho < 4; rho++)
#pragma unroll
        for (int jp = 0; jp < 4; jp++) {
          const int j0 = 8 * jp + rho, j1 = j0 + 4;
          b2[rho * 264 + 2 * jp] = pack2(WIN(j0, -1, 1), WIN(j1, -1, 1));
          b2[(4 + rho) * 264 + 2 * jp] = pack2(WIN(j0, -2, -2), WIN(j1, -2, -2));
        }
    }
    if (t0 < 1536) {
      const int qq0 = (t0 >> 3) + 16;
      const int e0 = qq0 & 15;
      uint32_t* b4 = pw + P_V4 + (qq0 & ~15) / 2 + 2 * ((e0 & 7) >> 1) + (e0 >> 3);
#pragma unroll
      for (int rho = 0; rho < 8; rho++)
#pragma unroll
        for (int jp = 0; jp < 2; jp++) {
          const int j0 = 16 * jp + rho, j1 = j0 + 8;
          b4[rho * 104 + 2 * jp] = pack2(WIN(j0, -2, 2), WIN(j1, -2, 2));
          b4[(8 + rho) * 104 + 2 * jp] = pack2(WIN(j0, -5, -3), WIN(j1, -5, -3));
        }
    }
    if (t0 < 1024) {
      const int qq0 = (t0 >> 4) + 16;
      const int e0 = qq0 & 15;
      uint32_t* b8 = pw + P_V8 + (qq0 & ~15) / 2 + 2 * ((e0 & 7) >> 1) + (e0 >> 3);
#pragma unroll
      for (int rho = 0; rho < 16; rho++) {
        b8[rho * 40] = pack2(WIN(rho, -4, 4), WIN(rho + 16, -4, 4));
        b8[(16 + rho) * 40] = pack2(WIN(rho, -11, -5), WIN(rho + 16, -11, -5));
      }
    }
#undef WIN
  }
  named_bar_sync(1 + ch, 64);
  if (tid == 0) TS(2, 2);

  float D[16][4];
#pragma unroll
  for (int j = 0; j < 16; j++)
#pragma unroll
    for (int q = 0; q < 4; q++) D[j][q] = 0.f;
  float* y1 = reinterpret_cast<float*>(pw + P_V2);
  if (half == 0) {
    uint32_t F[35];
    const uint32_t* fb = pw + P_TAP0 + ((g & 1) ? 152 : 0) + ((272 - g + 2 * t) >> 1);
#pragma unroll
    for (int m = 0; m < 35; m++) F[m] = fb[-4 * (m - 1)];
    const bf16* ub = uc + USEG * (1 + g) + 4 * t;
#pragma unroll
    for (int k = -16; k < 16; k++) {
      const uint2 b = *reinterpret_cast<const uint2*>(ub + (k < 0 ? 16 * k - 16 : 16 * k));
#pragma unroll
      for (int dl = 0; dl <= 16; dl++) {
        const int i = k + dl;
        if (i >= 0 && i < 16) mma_bf16(D[i], F[2 * dl + 1], F[2 * dl + 2], F[2 * dl], F[2 * dl + 1], b.x, b.y);
      }
    }
  } else {
#pragma unroll
    for (int p = 0; p < 2; p++) {
      uint32_t F[11];
      const uint32_t* fb = pw + P_TAPS + p * 112 + ((g & 1) ? 56 : 0) + ((144 - g + 2 * t) >> 1);
#pragma unroll
      for (int m = 0; m < 11; m++) F[m] = fb[-4 * (m + 7)];
      const uint32_t* vb = pw + P_V2 + (p * 4 + (g & 3)) * 264 + 2 * t;
      const int hh = g >> 2;
#pragma unroll
      for (int k = -8; k < 12; k++) {
        const int tile = k < -2 ? (hh ? k + 18 : 0) : k + 2 + 16 * hh;
        const uint2 b = *reinterpret_cast<const uint2*>(vb + 8 * tile);
#pragma unroll
        for (int dl = 4; dl <= 8; dl++) {
          const int i = k + dl;
          if (i >= 0 && i < 16) mma_bf16(D[i], F[2 * dl - 7], F[2 * dl - 6], F[2 * dl - 8], F[2 * dl - 7], b.x, b.y);
        }
      }
    }
    __syncwarp();
#pragma unroll
    for (int i = 0; i < 16; i++)
#pragma unroll
      for (int q = 0; q < 4; q++) {
        const int n = 2 * t + (q & 1);
        const int l = 4 * (16 * i + g + 8 * (q >> 1)) + 1024 * (n >> 2) + (n & 3);
        y1[l + 4 * (l >> 8)] = D[i][q];
        D[i][q] = 0.f;
      }
#pragma unroll
    for (int p = 0; p < 2; p++) {
      uint32_t F[11];
      const uint32_t* fb = pw + P_TAPS + (2 + p) * 112 + ((g & 1) ? 56 : 0) + ((144 - g + 2 * t) >> 1);
#pragma unroll
      for (int m = 0; m < 11; m++) F[m] = fb[-4 * (m + 7)];
      const uint32_t* vb = pw + P_V4 + (p * 8 + g) * 104 + 2 * t;
#pragma unroll
      for (int k = -1; k < 12; k++) {
        const uint2 b = *reinterpret_cast<const uint2*>(vb + 8 * (k + 1));
#pragma unroll
        for (int dl = 4; dl <= 8; dl++) {
          const int i = k + dl;
          if (i >= 0 && i < 16) mma_bf16(D[i], F[2 * dl - 7], F[2 * dl - 6], F[2 * dl - 8], F[2 * dl - 7], b.x, b.y);
        }
      }
    }
    __syncwarp();
#pragma unroll
    for (int i = 3; i < 16; i++)
#pragma unroll
      for (int q = 0; q < 4; q++) {
        const int l = 8 * (16 * i + g + 8 * (q >> 1)) + 2 * t + (q & 1);
        y1[l + 4 * (l >> 8)] += D[i][q];
        D[i][q] = 0.f;
      }
#pragma unroll
    for (int p = 0; p < 2; p++) {
      uint32_t F[11];
      const uint32_t* fb = pw + P_TAPS + (4 + p) * 112 + ((g & 1) ? 56 : 0) + ((144 - g + 2 * t) >> 1);
#pragma unroll
      for (int m = 0; m < 11; m++) F[m] = fb[-4 * (m + 7)];
#pragma unroll
      for (int nt = 0; nt < 2; nt++) {
        const uint32_t* vb = pw + P_V8 + (p * 16 + nt * 8 + g) * 40 + 2 * t;
#pragma unroll
        for (int k = -1; k < 4; k++) {
          const uint2 b = *reinterpret_cast<const uint2*>(vb + 8 * (k + 1));
#pragma unroll
          for (int dl = 4; dl <= 8; dl++) {
            const int i = k + dl;
            if (i >= 3 && i < 8) mma_bf16(D[2 * (i - 3) + nt], F[2 * dl - 7], F[2 * dl - 6], F[2 * dl - 8], F[2 * dl - 7], b.x, b.y);
          }
        }
      }
    }
    __syncwarp();
#pragma unroll
    for (int i = 3; i < 8; i++)
#pragma unroll
      for (int nt = 0; nt < 2; nt++)
#pragma unroll
        for (int q = 0; q < 4; q++) {
          const int l = 16 * (16 * i + g + 8 * (q >> 1)) + 8 * nt + 2 * t + (q & 1);
          y1[l + 4 * (l >> 8)] += D[2 * (i - 3) + nt][q];
        }
  }
  if (tid == 0) TS(2, 3);
  named_bar_sync(1 + ch, 64);
  float* y0 = reinterpret_cast<float*>(pw + P_V4);
  if (half == 0) {
#pragma unroll
    for (int i = 0; i < 16; i++)
#pragma unroll
      for (int q = 0; q < 4; q++) {
        const int l = 256 * (2 * t + (q & 1)) + 16 * i + g + 8 * (q >> 1);
        y0[l + 4 * (l >> 8)] = D[i][q];
      }
  }
  named_bar_sync(1 + ch, 64);
  {
    const float dsk = __bfloat162float(Dskip[d]);
    bf16* dst = g_bT + (size_t)d * SEQ;
#pragma unroll
    for (int it = 0; it < 4; it++) {
      const int l0 = (it * 64 + l64) * 8;
      const int o = l0 + 4 * (l0 >> 8);
      const float4 a0 = *reinterpret_cast<const float4*>(y0 + o), a1 = *reinterpret_cast<const float4*>(y0 + o + 4);
      const float4 c0 = *reinterpret_cast<const float4*>(y1 + o), c1 = *reinterpret_cast<const float4*>(y1 + o + 4);
      float y[8] = {a0.x + c0.x, a0.y + c0.y, a0.z + c0.z, a0.w + c0.w, a1.x + c1.x, a1.y + c1.y, a1.z + c1.z, a1.w + c1.w};
      uint32_t ow[4];
      float r[8];
#pragma unroll
      for (int q = 0; q < 8; q++) {
        const int l = l0 + q;
        auto U = [&](int tt) -> float {
          if (tt < 0) return 0.f;
          const int e = tt & 15;
          return __bfloat162float(uc[USEG * (1 + (tt >> 8)) + (tt & 240) + ((e & 7) >> 1) * 4 + (e >> 3) * 2 + (e & 1)]);
        };
        float yy = y[q];
        if (l0 >= 1016) yy -= k1024b * (U(l - 1020) + U(l - 1021));
        r[q] = bfr(yy) + bfr(U(l) * dsk);
      }
#pragma unroll
      for (int q = 0; q < 4; q++) ow[q] = pack2(r[2 * q], r[2 * q + 1]);
      *reinterpret_cast<uint4*>(dst + l0) = make_uint4(ow[0], ow[1], ow[2], ow[3]);
    }
  }
  if (tid == 0) TS(2, 4);
}

typedef CUresult (*EncodeFn)(CUtensorMap*, CUtensorMapDataType, cuuint32_t, void*, const cuuint64_t*, const cuuint64_t*,
                             const cuuint32_t*, const cuuint32_t*, CUtensorMapInterleave, CUtensorMapSwizzle,
                             CUtensorMapL2promotion, CUtensorMapFloatOOBfill);

static void make_map(EncodeFn enc, CUtensorMap* m, void* ptr, uint64_t inner, uint64_t outer, uint32_t bi, uint32_t bo) {
  cuuint64_t dims[2] = {inner, outer};
  cuuint64_t strides[1] = {inner * 2};
  cuuint32_t box[2] = {bi, bo};
  cuuint32_t es[2] = {1, 1};
  enc(m, CU_TENSOR_MAP_DATA_TYPE_BFLOAT16, 2, ptr, dims, strides, box, es, CU_TENSOR_MAP_INTERLEAVE_NONE,
      CU_TENSOR_MAP_SWIZZLE_128B, CU_TENSOR_MAP_L2_PROMOTION_L2_256B, CU_TENSOR_MAP_FLOAT_OOB_FILL_NONE);
}

extern "C" void kernel_launch(void* const* d_in, const int* in_sizes, int n_in, void* d_out, int out_size) {
  const bf16* x = (const bf16*)d_in[0];
  const bf16* wqkv = (const bf16*)d_in[1];
  const bf16* wo = (const bf16*)d_in[2];
  const bf16* logAr = (const bf16*)d_in[4];
  const bf16* Aim = (const bf16*)d_in[5];
  const bf16* Cre = (const bf16*)d_in[6];
  const bf16* Cim = (const bf16*)d_in[7];
  const bf16* logdt = (const bf16*)d_in[8];
  const bf16* Dskip = (const bf16*)d_in[9];
  const bf16* gatew = (const bf16*)d_in[10];

  static EncodeFn enc = nullptr;
  static void* p_o = nullptr;
  static void* p_bT = nullptr;
  if (!enc) {
    void* fn = nullptr;
    cudaDriverEntryPointQueryResult qr;
    cudaGetDriverEntryPoint("cuTensorMapEncodeTiled", &fn, cudaEnableDefault, &qr);
    enc = (EncodeFn)fn;
    cudaGetSymbolAddress(&p_o, g_o);
    cudaGetSymbolAddress(&p_bT, g_bT);
    cudaFuncSetAttribute(k1_qkv_attn, cudaFuncAttributeMaxDynamicSharedMemorySize, k1::SMEM);
    cudaFuncSetAttribute(k2_ssm, cudaFuncAttributeMaxDynamicSharedMemorySize, k2::SMEM);
    cudaFuncSetAttribute(k3_out, cudaFuncAttributeMaxDynamicSharedMemorySize, k3::SMEM);
  }
  CUtensorMap tmx, tmw, tmo, tmwo, tmbt, tmout;
  make_map(enc, &tmx, (void*)x, 1024, 2048, 64, 128);
  make_map(enc, &tmw, (void*)wqkv, 3072, 1024, 64, 64);
  make_map(enc, &tmo, p_o, 1024, 2048, 64, 64);
  make_map(enc, &tmwo, (void*)wo, 1024, 1024, 64, 64);
  make_map(enc, &tmbt, p_bT, 2048, 1024, 64, 128);
  make_map(enc, &tmout, d_out, 1024, 2048, 64, 64);

  k2_ssm<<<128, 512, k2::SMEM>>>(x, logAr, Aim, Cre, Cim, logdt, Dskip, gatew);
  cudaLaunchAttribute at[1];
  at[0].id = cudaLaunchAttributeProgrammaticStreamSerialization;
  at[0].val.programmaticStreamSerializationAllowed = 1;
  cudaLaunchConfig_t cfg = {};
  cfg.gridDim = dim3(128); cfg.blockDim = dim3(384); cfg.stream = cudaStreamPerThread; cfg.attrs = at; cfg.numAttrs = 1;
  cfg.dynamicSmemBytes = k1::SMEM;
  cudaLaunchKernelEx(&cfg, k1_qkv_attn, tmx, tmw);
  cfg.dynamicSmemBytes = k3::SMEM;
  cudaLaunchKernelEx(&cfg, k3_out, tmo, tmwo, tmbt, tmout);
}
```

```cpp
#include <cuda_runtime.h>
#include <cuda_bf16.h>
#include <cuda.h>
#include <stdint.h>

typedef __nv_bfloat16 bf16;

constexpr int SEQ = 2048, DM = 1024, NMODE = 128;

__device__ __align__(1024) bf16 g_o[SEQ * DM];
__device__ __align__(1024) bf16 g_b[SEQ * DM];
__device__ float g_gate[SEQ];
__device__ __align__(16) float g_part[16 * 8 * 2 * 1056];
__device__ unsigned int g_cnt[16];

#define TS(k, i) do {} while (0)
__device__ __forceinline__ uint32_t smem_u32(const void* p) { return (uint32_t)__cvta_generic_to_shared(p); }
__device__ __forceinline__ void mbar_init(uint32_t bar, uint32_t cnt) {
  asm volatile("mbarrier.init.shared::cta.b64 [%0], %1;" ::"r"(bar), "r"(cnt));
}
__device__ __forceinline__ void mbar_expect_tx(uint32_t bar, uint32_t bytes) {
  asm volatile("mbarrier.arrive.expect_tx.shared::cta.b64 _, [%0], %1;" ::"r"(bar), "r"(bytes) : "memory");
}
__device__ __forceinline__ void mbar_arrive_cluster(uint32_t bar, uint32_t cta) {
  asm volatile(
      "{\n.reg .b32 ra;\nmapa.shared::cluster.u32 ra, %0, %1;\n"
      "mbarrier.arrive.shared::cluster.b64 _, [ra];\n}\n" ::"r"(bar), "r"(cta) : "memory");
}
__device__ __forceinline__ bool mbar_try_wait(uint32_t bar, uint32_t parity) {
  uint32_t ok;
  asm volatile(
      "{\n.reg .pred p;\nmbarrier.try_wait.parity.shared::cta.b64 p, [%1], %2;\nselp.u32 %0, 1, 0, p;\n}\n"
      : "=r"(ok) : "r"(bar), "r"(parity) : "memory");
  return ok;
}
__device__ __forceinline__ void mbar_wait(uint32_t bar, uint32_t parity) {
  while (!mbar_try_wait(bar, parity)) {}
}
__device__ __forceinline__ void tma_load_2d(uint32_t dst, const CUtensorMap* map, uint32_t bar, int c0, int c1) {
  asm volatile(
      "cp.async.bulk.tensor.2d.shared::cluster.global.mbarrier::complete_tx::bytes [%0], [%1, {%3, %4}], [%2];" ::"r"(dst),
      "l"(map), "r"(bar), "r"(c0), "r"(c1) : "memory");
}
__device__ __forceinline__ void tma_load_2d_mc(uint32_t dst, const CUtensorMap* map, uint32_t bar, int c0, int c1,
                                               uint16_t mask) {
  asm volatile(
      "cp.async.bulk.tensor.2d.shared::cluster.global.mbarrier::complete_tx::bytes.multicast::cluster [%0], [%1, {%3, %4}], [%2], %5;" ::"r"(dst),
      "l"(map), "r"(bar), "r"(c0), "r"(c1), "h"(mask) : "memory");
}
__device__ __forceinline__ void cluster_sync_all() {
  asm volatile("barrier.cluster.arrive.release.aligned;\nbarrier.cluster.wait.acquire.aligned;\n" ::: "memory");
}
__device__ __forceinline__ uint32_t cluster_ctarank() {
  uint32_t r; asm volatile("mov.u32 %0, %%cluster_ctarank;" : "=r"(r)); return r;
}
__device__ __forceinline__ void pdl_wait() { asm volatile("griddepcontrol.wait;" ::: "memory"); }
__device__ __forceinline__ void pdl_launch() { asm volatile("griddepcontrol.launch_dependents;" ::: "memory"); }
__device__ __forceinline__ void named_bar_sync(int id, int n) { asm volatile("bar.sync %0, %1;" ::"r"(id), "r"(n) : "memory"); }
__device__ __forceinline__ void fence_async_smem() { asm volatile("fence.proxy.async.shared::cta;" ::: "memory"); }
__device__ __forceinline__ void wg_fence() { asm volatile("wgmma.fence.sync.aligned;" ::: "memory"); }
__device__ __forceinline__ void wg_commit() { asm volatile("wgmma.commit_group.sync.aligned;" ::: "memory"); }
template <int N> __device__ __forceinline__ void wg_wait() { asm volatile("wgmma.wait_group.sync.aligned %0;" ::"n"(N) : "memory"); }
__device__ __forceinline__ uint64_t make_desc(uint32_t addr, uint32_t lbo, uint32_t sbo) {
  return (uint64_t)((addr & 0x3FFFF) >> 4) | ((uint64_t)(lbo >> 4) << 16) | ((uint64_t)(sbo >> 4) << 32) | (1ull << 62);
}
__device__ __forceinline__ float bfr(float x) { return __bfloat162float(__float2bfloat16_rn(x)); }
__device__ __forceinline__ uint32_t pack2(float lo, float hi) {
  __nv_bfloat162 v = __floats2bfloat162_rn(lo, hi);
  return *reinterpret_cast<uint32_t*>(&v);
}
__device__ __forceinline__ float ex2f(float x) { float r; asm("ex2.approx.ftz.f32 %0, %1;" : "=f"(r) : "f"(x)); return r; }
__device__ __forceinline__ float lo_f(uint32_t v) { return __uint_as_float(v << 16); }
__device__ __forceinline__ float hi_f(uint32_t v) { return __uint_as_float(v & 0xffff0000u); }
__device__ __forceinline__ uint32_t phi2(float a0, float a1) {
  const uint32_t t2 = pack2(a0, a1);
  const float t0 = lo_f(t2), t1 = hi_f(t2);
  const float e0 = ex2f(t0 * 1.4426950408889634f), e1 = ex2f(t1 * 1.4426950408889634f);
  const float f0 = t0 > 0.f ? t0 + 1.0f : e0;
  const float f1 = t1 > 0.f ? t1 + 1.0f : e1;
  const uint32_t f2 = pack2(f0, f1);
  return pack2(lo_f(f2) + 1e-6f, hi_f(f2) + 1e-6f);
}
template <int R> __device__ __forceinline__ void fence_regs(float (&d)[R]) {
#pragma unroll
  for (int i = 0; i < R; i++) asm volatile("" : "+f"(d[i])::"memory");
}

__device__ __forceinline__ void wgmma_ss_n192_tb(float (&d)[96], uint64_t da, uint64_t db, int sc) {
  asm volatile("{\n.reg .pred p;\nsetp.ne.b32 p, %98, 0;\n"
    "wgmma.mma_async.sync.aligned.m64n192k16.f32.bf16.bf16 {%0, %1, %2, %3, %4, %5, %6, %7, %8, %9, %10, %11, %12, %13, %14, %15, %16, %17, %18, %19, %20, %21, %22, %23, %24, %25, %26, %27, %28, %29, %30, %31, %32, %33, %34, %35, %36, %37, %38, %39, %40, %41, %42, %43, %44, %45, %46, %47, %48, %49, %50, %51, %52, %53, %54, %55, %56, %57, %58, %59, %60, %61, %62, %63, %64, %65, %66, %67, %68, %69, %70, %71, %72, %73, %74, %75, %76, %77, %78, %79, %80, %81, %82, %83, %84, %85, %86, %87, %88, %89, %90, %91, %92, %93, %94, %95}, %96, %97, p, 1, 1, 0, 1;\n}\n"
    : "+f"(d[0]), "+f"(d[1]), "+f"(d[2]), "+f"(d[3]), "+f"(d[4]), "+f"(d[5]), "+f"(d[6]), "+f"(d[7]), "+f"(d[8]), "+f"(d[9]), "+f"(d[10]), "+f"(d[11]), "+f"(d[12]), "+f"(d[13]), "+f"(d[14]), "+f"(d[15]), "+f"(d[16]), "+f"(d[17]), "+f"(d[18]), "+f"(d[19]), "+f"(d[20]), "+f"(d[21]), "+f"(d[22]), "+f"(d[23]), "+f"(d[24]), "+f"(d[25]), "+f"(d[26]), "+f"(d[27]), "+f"(d[28]), "+f"(d[29]), "+f"(d[30]), "+f"(d[31]), "+f"(d[32]), "+f"(d[33]), "+f"(d[34]), "+f"(d[35]), "+f"(d[36]), "+f"(d[37]), "+f"(d[38]), "+f"(d[39]), "+f"(d[40]), "+f"(d[41]), "+f"(d[42]), "+f"(d[43]), "+f"(d[44]), "+f"(d[45]), "+f"(d[46]), "+f"(d[47]), "+f"(d[48]), "+f"(d[49]), "+f"(d[50]), "+f"(d[51]), "+f"(d[52]), "+f"(d[53]), "+f"(d[54]), "+f"(d[55]), "+f"(d[56]), "+f"(d[57]), "+f"(d[58]), "+f"(d[59]), "+f"(d[60]), "+f"(d[61]), "+f"(d[62]), "+f"(d[63]), "+f"(d[64]), "+f"(d[65]), "+f"(d[66]), "+f"(d[67]), "+f"(d[68]), "+f"(d[69]), "+f"(d[70]), "+f"(d[71]), "+f"(d[72]), "+f"(d[73]), "+f"(d[74]), "+f"(d[75]), "+f"(d[76]), "+f"(d[77]), "+f"(d[78]), "+f"(d[79]), "+f"(d[80]), "+f"(d[81]), "+f"(d[82]), "+f"(d[83]), "+f"(d[84]), "+f"(d[85]), "+f"(d[86]), "+f"(d[87]), "+f"(d[88]), "+f"(d[89]), "+f"(d[90]), "+f"(d[91]), "+f"(d[92]), "+f"(d[93]), "+f"(d[94]), "+f"(d[95])
    : "l"(da), "l"(db), "r"(sc));
}

__device__ __forceinline__ void wgmma_ss_n128_tb(float (&d)[64], uint64_t da, uint64_t db, int sc) {
  asm volatile("{\n.reg .pred p;\nsetp.ne.b32 p, %66, 0;\n"
    "wgmma.mma_async.sync.aligned.m64n128k16.f32.bf16.bf16 {%0, %1, %2, %3, %4, %5, %6, %7, %8, %9, %10, %11, %12, %13, %14, %15, %16, %17, %18, %19, %20, %21, %22, %23, %24, %25, %26, %27, %28, %29, %30, %31, %32, %33, %34, %35, %36, %37, %38, %39, %40, %41, %42, %43, %44, %45, %46, %47, %48, %49, %50, %51, %52, %53, %54, %55, %56, %57, %58, %59, %60, %61, %62, %63}, %64, %65, p, 1, 1, 0, 1;\n}\n"
    : "+f"(d[0]), "+f"(d[1]), "+f"(d[2]), "+f"(d[3]), "+f"(d[4]), "+f"(d[5]), "+f"(d[6]), "+f"(d[7]), "+f"(d[8]), "+f"(d[9]), "+f"(d[10]), "+f"(d[11]), "+f"(d[12]), "+f"(d[13]), "+f"(d[14]), "+f"(d[15]), "+f"(d[16]), "+f"(d[17]), "+f"(d[18]), "+f"(d[19]), "+f"(d[20]), "+f"(d[21]), "+f"(d[22]), "+f"(d[23]), "+f"(d[24]), "+f"(d[25]), "+f"(d[26]), "+f"(d[27]), "+f"(d[28]), "+f"(d[29]), "+f"(d[30]), "+f"(d[31]), "+f"(d[32]), "+f"(d[33]), "+f"(d[34]), "+f"(d[35]), "+f"(d[36]), "+f"(d[37]), "+f"(d[38]), "+f"(d[39]), "+f"(d[40]), "+f"(d[41]), "+f"(d[42]), "+f"(d[43]), "+f"(d[44]), "+f"(d[45]), "+f"(d[46]), "+f"(d[47]), "+f"(d[48]), "+f"(d[49]), "+f"(d[50]), "+f"(d[51]), "+f"(d[52]), "+f"(d[53]), "+f"(d[54]), "+f"(d[55]), "+f"(d[56]), "+f"(d[57]), "+f"(d[58]), "+f"(d[59]), "+f"(d[60]), "+f"(d[61]), "+f"(d[62]), "+f"(d[63])
    : "l"(da), "l"(db), "r"(sc));
}

__device__ __forceinline__ void wgmma_ss_n64_tatb(float (&d)[32], uint64_t da, uint64_t db, int sc) {
  asm volatile("{\n.reg .pred p;\nsetp.ne.b32 p, %34, 0;\n"
    "wgmma.mma_async.sync.aligned.m64n64k16.f32.bf16.bf16 {%0, %1, %2, %3, %4, %5, %6, %7, %8, %9, %10, %11, %12, %13, %14, %15, %16, %17, %18, %19, %20, %21, %22, %23, %24, %25, %26, %27, %28, %29, %30, %31}, %32, %33, p, 1, 1, 1, 1;\n}\n"
    : "+f"(d[0]), "+f"(d[1]), "+f"(d[2]), "+f"(d[3]), "+f"(d[4]), "+f"(d[5]), "+f"(d[6]), "+f"(d[7]), "+f"(d[8]), "+f"(d[9]), "+f"(d[10]), "+f"(d[11]), "+f"(d[12]), "+f"(d[13]), "+f"(d[14]), "+f"(d[15]), "+f"(d[16]), "+f"(d[17]), "+f"(d[18]), "+f"(d[19]), "+f"(d[20]), "+f"(d[21]), "+f"(d[22]), "+f"(d[23]), "+f"(d[24]), "+f"(d[25]), "+f"(d[26]), "+f"(d[27]), "+f"(d[28]), "+f"(d[29]), "+f"(d[30]), "+f"(d[31])
    : "l"(da), "l"(db), "r"(sc));
}

__device__ __forceinline__ void wgmma_ss_n8_tatb(float (&d)[4], uint64_t da, uint64_t db, int sc) {
  asm volatile("{\n.reg .pred p;\nsetp.ne.b32 p, %6, 0;\n"
    "wgmma.mma_async.sync.aligned.m64n8k16.f32.bf16.bf16 {%0, %1, %2, %3}, %4, %5, p, 1, 1, 1, 1;\n}\n"
    : "+f"(d[0]), "+f"(d[1]), "+f"(d[2]), "+f"(d[3])
    : "l"(da), "l"(db), "r"(sc));
}

__device__ __forceinline__ void wgmma_rs_n40_tb(float (&d)[20], uint32_t a0, uint32_t a1, uint32_t a2, uint32_t a3, uint64_t db, int sc) {
  asm volatile("{\n.reg .pred p;\nsetp.ne.b32 p, %25, 0;\n"
    "wgmma.mma_async.sync.aligned.m64n40k16.f32.bf16.bf16 {%0, %1, %2, %3, %4, %5, %6, %7, %8, %9, %10, %11, %12, %13, %14, %15, %16, %17, %18, %19}, {%20, %21, %22, %23}, %24, p, 1, 1, 1;\n}\n"
    : "+f"(d[0]), "+f"(d[1]), "+f"(d[2]), "+f"(d[3]), "+f"(d[4]), "+f"(d[5]), "+f"(d[6]), "+f"(d[7]), "+f"(d[8]), "+f"(d[9]), "+f"(d[10]), "+f"(d[11]), "+f"(d[12]), "+f"(d[13]), "+f"(d[14]), "+f"(d[15]), "+f"(d[16]), "+f"(d[17]), "+f"(d[18]), "+f"(d[19])
    : "r"(a0), "r"(a1), "r"(a2), "r"(a3), "l"(db), "r"(sc));
}

namespace k1 {
constexpr int BM = 256, BN = 192, BK = 64, ST = 4;
constexpr int A_BYTES = BM * BK * 2, B_BYTES = BK * BN * 2, STAGE = A_BYTES + B_BYTES;
constexpr int SMEM = ST * STAGE + 1024 + 256;
constexpr int OFF_PK = 0, OFF_V = 32768, OFF_ONES = 65536, OFF_KV = 69632, OFF_O = 81920, OFF_RED = 114688;
}

__global__ void __cluster_dims__(2, 1, 1) __launch_bounds__(384, 1)
k1_qkv_attn(const __grid_constant__ CUtensorMap tmx, const __grid_constant__ CUtensorMap tmw) {
  using namespace k1;
  extern __shared__ uint8_t smem_raw[];
  const uint32_t sbase = (smem_u32(smem_raw) + 1023) & ~1023u;
  uint8_t* sgen = smem_raw + (sbase - smem_u32(smem_raw));
  const uint32_t bars = sbase + ST * STAGE;
  const int tid = threadIdx.x, warp = tid >> 5, lane = tid & 31;
  const uint32_t rank = cluster_ctarank();
  const int cl = blockIdx.x >> 1;
  const int mt = cl >> 3;
  const int hp = ((cl & 7) << 1) + rank;
  const int m0 = mt * BM;

  if (tid == 0) {
    for (int s = 0; s < ST; s++) {
      mbar_init(bars + 8 * s, 1);
      mbar_init(bars + 8 * (ST + s), 16);
    }
    asm volatile("fence.mbarrier_init.release.cluster;" ::: "memory");
  }
  cluster_sync_all();
  pdl_launch();

  if (warp >= 8) {
    asm volatile("setmaxnreg.dec.sync.aligned.u32 40;");
    if (warp == 8 && lane == 0) {
      for (int kb = 0; kb < DM / BK; kb++) {
        const int s = kb % ST;
        mbar_wait(bars + 8 * (ST + s), ((kb / ST) & 1) ^ 1);
        const uint32_t full = bars + 8 * s;
        mbar_expect_tx(full, STAGE);
        const uint32_t sa = sbase + s * STAGE, sb = sa + A_BYTES;
        tma_load_2d_mc(sa + rank * 16384, &tmx, full, kb * BK, m0 + rank * 128, (uint16_t)3);
#pragma unroll
        for (int j = 0; j < 3; j++) tma_load_2d(sb + j * 8192, &tmw, full, j * 1024 + hp * 64, kb * BK);
      }
      pdl_wait();
    }
    cluster_sync_all();
  } else {
    asm volatile("setmaxnreg.inc.sync.aligned.u32 232;");
    const int wg = warp >> 2, w4 = warp & 3, g = lane >> 2, t = lane & 3;
    if (tid == 0) TS(1, 0);
    float acc[2][96];
#pragma unroll
    for (int i = 0; i < 96; i++) { acc[0][i] = 0.f; acc[1][i] = 0.f; }
    for (int kb = 0; kb < DM / BK; kb++) {
      const int s = kb % ST;
      mbar_wait(bars + 8 * s, (kb / ST) & 1);
      const uint32_t sa = sbase + s * STAGE + wg * 16384, sb = sbase + s * STAGE + A_BYTES;
      wg_fence();
#pragma unroll
      for (int ks = 0; ks < 4; ks++) {
        const uint64_t db = make_desc(sb + ks * 2048, 8192, 1024);
#pragma unroll
        for (int mb = 0; mb < 2; mb++) {
          const uint64_t da = make_desc(sa + mb * 8192 + ks * 32, 16, 1024);
          wgmma_ss_n192_tb(acc[mb], da, db, 1);
        }
      }
      wg_commit();
      if (kb > 0) {
        wg_wait<1>();
        const int sp = (kb - 1) % ST;
        if (lane == 0) { mbar_arrive_cluster(bars + 8 * (ST + sp), 0); mbar_arrive_cluster(bars + 8 * (ST + sp), 1); }
      }
    }
    wg_wait<0>();
    fence_regs(acc[0]); fence_regs(acc[1]);
    if (tid == 0) TS(1, 1);
    named_bar_sync(1, 256);

#pragma unroll
    for (int mb = 0; mb < 2; mb++) {
#pragma unroll
      for (int h = 0; h < 2; h++) {
        const int r = wg * 128 + mb * 64 + w4 * 16 + g + h * 8;
#pragma unroll
        for (int j = 0; j < 8; j++) {
          const uint32_t off = r * 128 + ((j ^ (r & 7)) << 4) + t * 4;
          const float k0 = acc[mb][4 * (8 + j) + 2 * h], k1v = acc[mb][4 * (8 + j) + 2 * h + 1];
          const float v0 = acc[mb][4 * (16 + j) + 2 * h], v1 = acc[mb][4 * (16 + j) + 2 * h + 1];
          *reinterpret_cast<uint32_t*>(sgen + OFF_PK + off) = phi2(k0, k1v);
          *reinterpret_cast<uint32_t*>(sgen + OFF_V + off) = pack2(v0, v1);
        }
      }
    }
    if (tid < 256) *reinterpret_cast<uint32_t*>(sgen + OFF_ONES + tid * 4) = 0x3F803F80u;
    fence_async_smem();
    named_bar_sync(1, 256);

    if (tid == 0) TS(1, 2);
    float* part = g_part + (size_t)(hp * 8 + mt) * 2112;
    {
      float kv[32], zz[4];
#pragma unroll
      for (int i = 0; i < 32; i++) kv[i] = 0.f;
#pragma unroll
      for (int i = 0; i < 4; i++) zz[i] = 0.f;
      wg_fence();
#pragma unroll
      for (int ks = 0; ks < 8; ks++) {
        const uint64_t da = make_desc(sbase + OFF_PK + wg * 16384 + ks * 2048, 16, 1024);
        const uint64_t db = make_desc(sbase + OFF_V + wg * 16384 + ks * 2048, 16, 1024);
        const uint64_t d1 = make_desc(sbase + OFF_ONES, 16, 0);
        wgmma_ss_n64_tatb(kv, da, db, 1);
        wgmma_ss_n8_tatb(zz, da, d1, 1);
      }
      wg_commit();
      wg_wait<0>();
      fence_regs(kv); fence_regs(zz);
      const int hh = w4 >> 1;
      float* red = reinterpret_cast<float*>(sgen + OFF_RED);
      float vals[2][4][2];
#pragma unroll
      for (int h = 0; h < 2; h++)
#pragma unroll
        for (int j = 0; j < 4; j++) {
          vals[h][j][0] = hh ? kv[4 * (4 + j) + 2 * h] : kv[4 * j + 2 * h];
          vals[h][j][1] = hh ? kv[4 * (4 + j) + 2 * h + 1] : kv[4 * j + 2 * h + 1];
        }
      if (wg == 1) {
#pragma unroll
        for (int h = 0; h < 2; h++) {
          const int d = (w4 & 1) * 16 + g + h * 8;
#pragma unroll
          for (int j = 0; j < 4; j++)
            *reinterpret_cast<float2*>(red + hh * 1056 + d * 32 + 8 * j + 2 * t) = make_float2(vals[h][j][0], vals[h][j][1]);
          if (t == 0) red[hh * 1056 + 1024 + d] = zz[2 * h];
        }
      }
      named_bar_sync(1, 256);
      if (wg == 0) {
#pragma unroll
        for (int h = 0; h < 2; h++) {
          const int d = (w4 & 1) * 16 + g + h * 8;
#pragma unroll
          for (int j = 0; j < 4; j++) {
            const float2 o = *reinterpret_cast<const float2*>(red + hh * 1056 + d * 32 + 8 * j + 2 * t);
            *reinterpret_cast<float2*>(part + hh * 1056 + d * 32 + 8 * j + 2 * t) = make_float2(vals[h][j][0] + o.x, vals[h][j][1] + o.y);
          }
          if (t == 0) part[hh * 1056 + 1024 + d] = zz[2 * h] + red[hh * 1056 + 1024 + d];
        }
        __threadfence();
        named_bar_sync(2, 128);
        if (tid == 0) atomicAdd(&g_cnt[hp], 1u);
      }
    }
    if (tid == 0) TS(1, 3);
    uint32_t pq[2][4][4];
#pragma unroll
    for (int mb = 0; mb < 2; mb++)
#pragma unroll
      for (int kk = 0; kk < 4; kk++) {
        pq[mb][kk][0] = phi2(acc[mb][8 * kk + 0], acc[mb][8 * kk + 1]);
        pq[mb][kk][1] = phi2(acc[mb][8 * kk + 2], acc[mb][8 * kk + 3]);
        pq[mb][kk][2] = phi2(acc[mb][8 * kk + 4], acc[mb][8 * kk + 5]);
        pq[mb][kk][3] = phi2(acc[mb][8 * kk + 6], acc[mb][8 * kk + 7]);
      }
    if (tid == 0) TS(1, 4);
    if (tid == 0) {
      unsigned int v;
      do { asm volatile("ld.acquire.gpu.global.u32 %0, [%1];" : "=r"(v) : "l"(&g_cnt[hp]) : "memory"); } while (v < 8u);
    }
    named_bar_sync(1, 256);
    {
      if (tid == 0) TS(1, 5);
      const float* pb = g_part + (size_t)(hp * 8) * 2112;
      for (int i = tid; i < 528; i += 256) {
        float4 s4 = make_float4(0.f, 0.f, 0.f, 0.f);
#pragma unroll
        for (int p = 0; p < 8; p++) {
          float4 v4 = __ldcg(reinterpret_cast<const float4*>(pb + p * 2112) + i);
          s4.x += v4.x; s4.y += v4.y; s4.z += v4.z; s4.w += v4.w;
        }
        const int hh = i / 264, rem = i - hh * 264;
        uint8_t* tile = sgen + OFF_KV + hh * 4096;
        if (rem < 256) {
          const int d = rem >> 3, e = (rem & 7) * 4;
          const uint32_t off = d * 128 + (((e >> 3) ^ (d & 7)) << 4) + (e & 7) * 2;
          *reinterpret_cast<uint2*>(tile + off) = make_uint2(pack2(s4.x, s4.y), pack2(s4.z, s4.w));
        } else {
          const int d0 = (rem - 256) * 4;
          float zv[4] = {s4.x, s4.y, s4.z, s4.w};
#pragma unroll
          for (int q = 0; q < 4; q++) {
            const int d = d0 + q;
            const uint32_t off = d * 128 + ((4 ^ (d & 7)) << 4);
            *reinterpret_cast<uint4*>(tile + off) = make_uint4(pack2(zv[q], 0.f), 0u, 0u, 0u);
          }
        }
      }
    }
    fence_async_smem();
    named_bar_sync(1, 256);
    if (tid == 0) TS(1, 6);
#pragma unroll
    for (int mb = 0; mb < 2; mb++) {
#pragma unroll
      for (int hh = 0; hh < 2; hh++) {
        float num[20];
#pragma unroll
        for (int i = 0; i < 20; i++) num[i] = 0.f;
        wg_fence();
#pragma unroll
        for (int kk = 0; kk < 2; kk++) {
          const uint64_t db = make_desc(sbase + OFF_KV + hh * 4096 + kk * 2048, 16, 1024);
          wgmma_rs_n40_tb(num, pq[mb][hh * 2 + kk][0], pq[mb][hh * 2 + kk][1], pq[mb][hh * 2 + kk][2], pq[mb][hh * 2 + kk][3], db, 1);
        }
        wg_commit();
        wg_wait<0>();
        fence_regs(num);
#pragma unroll
        for (int h = 0; h < 2; h++) {
          float den = __shfl_sync(0xffffffffu, num[16 + 2 * h], lane & ~3);
          den = bfr(bfr(den) + 1e-6f);
          const float rden = 1.0f / den;
          const int r = wg * 128 + mb * 64 + w4 * 16 + g + h * 8;
#pragma unroll
          for (int j = 0; j < 4; j++) {
            const uint32_t n2 = pack2(num[4 * j + 2 * h], num[4 * j + 2 * h + 1]);
            const float o0 = lo_f(n2) * rden, o1 = hi_f(n2) * rden;
            const uint32_t off = r * 128 + (((hh * 4 + j) ^ (r & 7)) << 4) + t * 4;
            *reinterpret_cast<uint32_t*>(sgen + OFF_O + off) = pack2(o0, o1);
          }
        }
      }
    }
    named_bar_sync(1, 256);
    if (tid == 0) TS(1, 7);
    for (int i = tid; i < 256 * 8; i += 256) {
      const int r = i >> 3, c = i & 7;
      uint4 v = *reinterpret_cast<const uint4*>(sgen + OFF_O + r * 128 + ((c ^ (r & 7)) << 4));
      *reinterpret_cast<uint4*>(g_o + (size_t)(m0 + r) * DM + hp * 64 + c * 8) = v;
    }
    if (tid == 0) TS(1, 8);
    cluster_sync_all();
  }
}

namespace k3 {
constexpr int BM = 128, BN = 128, BK = 64, ST = 5;
constexpr int A_BYTES = BM * BK * 2, B_BYTES = BK * BN * 2, STAGE = A_BYTES + B_BYTES;
constexpr int OFF_BT = ST * STAGE;
constexpr int OFF_BAR = OFF_BT + 32768;
constexpr int SMEM = OFF_BAR + 1024 + 256;
}

__global__ void __cluster_dims__(2, 1, 1) __launch_bounds__(384, 1)
k3_out(const __grid_constant__ CUtensorMap tmo, const __grid_constant__ CUtensorMap tmw,
       const __grid_constant__ CUtensorMap tmbt, const __grid_constant__ CUtensorMap tmout) {
  using namespace k3;
  extern __shared__ uint8_t smem_raw[];
  const uint32_t sbase = (smem_u32(smem_raw) + 1023) & ~1023u;
  uint8_t* sgen = smem_raw + (sbase - smem_u32(smem_raw));
  const uint32_t bars = sbase + OFF_BAR;
  const uint32_t barbt = bars + 8 * 2 * ST;
  const int tid = threadIdx.x, warp = tid >> 5, lane = tid & 31;
  const uint32_t rank = cluster_ctarank();
  const int cl = blockIdx.x >> 1;
  const int mt = cl >> 2;
  const int nt = ((cl & 3) << 1) + rank;
  const int m0 = mt * BM, n0 = nt * BN;

  if (tid == 0) {
    for (int s = 0; s < ST; s++) {
      mbar_init(bars + 8 * s, 1);
      mbar_init(bars + 8 * (ST + s), 16);
    }
    mbar_init(barbt, 1);
    asm volatile("fence.mbarrier_init.release.cluster;" ::: "memory");
  }
  cluster_sync_all();

  if (warp >= 8) {
    asm volatile("setmaxnreg.dec.sync.aligned.u32 40;");
    if (warp == 8 && lane == 0) {
      for (int kb = 0; kb < ST; kb++) {
        const uint32_t full = bars + 8 * kb;
        mbar_expect_tx(full, STAGE);
        const uint32_t sb = sbase + kb * STAGE + A_BYTES;
#pragma unroll
        for (int j = 0; j < 2; j++) tma_load_2d(sb + j * 8192, &tmw, full, n0 + j * 64, kb * BK);
      }
      pdl_wait();
      if (blockIdx.x == 0) for (int i = 0; i < 16; i++) g_cnt[i] = 0;
      for (int kb = 0; kb < DM / BK; kb++) {
        const int s = kb % ST;
        const uint32_t full = bars + 8 * s;
        const uint32_t sa = sbase + s * STAGE, sb = sa + A_BYTES;
        if (kb >= ST) {
          mbar_wait(bars + 8 * (ST + s), ((kb / ST) & 1) ^ 1);
          mbar_expect_tx(full, STAGE);
#pragma unroll
          for (int j = 0; j < 2; j++) tma_load_2d(sb + j * 8192, &tmw, full, n0 + j * 64, kb * BK);
        }
        tma_load_2d_mc(sa + rank * 8192, &tmo, full, kb * BK, m0 + rank * 64, (uint16_t)3);
        if (kb == 2) {
          mbar_expect_tx(barbt, 32768);
          tma_load_2d(sbase + OFF_BT, &tmbt, barbt, m0, n0);
          tma_load_2d(sbase + OFF_BT + 16384, &tmbt, barbt, m0 + 64, n0);
        }
      }
    }
    cluster_sync_all();
  } else {
    asm volatile("setmaxnreg.inc.sync.aligned.u32 232;");
    const int wg = warp >> 2, w4 = warp & 3, g = lane >> 2, t = lane & 3;
    if (tid == 0) TS(3, 0);
    float acc[64];
#pragma unroll
    for (int i = 0; i < 64; i++) acc[i] = 0.f;
    for (int kb = 0; kb < DM / BK; kb++) {
      const int s = kb % ST;
      mbar_wait(bars + 8 * s, (kb / ST) & 1);
      const uint32_t sa = sbase + s * STAGE + wg * 8192, sb = sbase + s * STAGE + A_BYTES;
      wg_fence();
#pragma unroll
      for (int ks = 0; ks < 4; ks++) {
        const uint64_t db = make_desc(sb + ks * 2048, 8192, 1024);
        const uint64_t da = make_desc(sa + ks * 32, 16, 1024);
        wgmma_ss_n128_tb(acc, da, db, 1);
      }
      wg_commit();
      if (kb > 0) {
        wg_wait<1>();
        const int sp = (kb - 1) % ST;
        if (lane == 0) { mbar_arrive_cluster(bars + 8 * (ST + sp), 0); mbar_arrive_cluster(bars + 8 * (ST + sp), 1); }
      }
    }
    wg_wait<0>();
    fence_regs(acc);
    if (tid == 0) TS(3, 1);
    named_bar_sync(1, 256);
    mbar_wait(barbt, 0);
    pdl_wait();
#pragma unroll
    for (int h = 0; h < 2; h++) {
      const int rl = wg * 64 + w4 * 16 + g + h * 8;
      const float gt = g_gate[m0 + rl];
      const float omg = bfr(1.0f - gt);
      const uint8_t* bt = sgen + OFF_BT + wg * 16384;
      const int ll = rl & 63;
#pragma unroll
      for (int j = 0; j < 16; j++) {
        const int c = 8 * j + 2 * t;
        const float b0 = __bfloat162float(*reinterpret_cast<const bf16*>(bt + c * 128 + (((ll >> 3) ^ (c & 7)) << 4) + (ll & 7) * 2));
        const float b1 = __bfloat162float(*reinterpret_cast<const bf16*>(bt + (c + 1) * 128 + (((ll >> 3) ^ ((c + 1) & 7)) << 4) + (ll & 7) * 2));
        const uint32_t a2 = pack2(acc[4 * j + 2 * h], acc[4 * j + 2 * h + 1]);
        const float o0 = bfr(gt * lo_f(a2)) + bfr(omg * b0);
        const float o1 = bfr(gt * hi_f(a2)) + bfr(omg * b1);
        *reinterpret_cast<uint32_t*>(sgen + (j >> 3) * 16384 + rl * 128 + (((j & 7) ^ (rl & 7)) << 4) + t * 4) = pack2(o0, o1);
      }
    }
    fence_async_smem();
    if (tid == 0) TS(3, 2);
    named_bar_sync(2 + wg, 128);
    if ((tid & 127) == 0) {
#pragma unroll
      for (int j = 0; j < 2; j++)
        asm volatile("cp.async.bulk.tensor.2d.global.shared::cta.bulk_group [%0, {%2, %3}], [%1];" ::"l"(&tmout),
                     "r"(sbase + j * 16384 + wg * 8192), "r"(n0 + j * 64), "r"(m0 + wg * 64) : "memory");
      asm volatile("cp.async.bulk.commit_group;" ::: "memory");
      asm volatile("cp.async.bulk.wait_group.read 0;" ::: "memory");
      if (tid == 0) TS(3, 3);
    }
    cluster_sync_all();
  }
}

__device__ __align__(1024) bf16 g_bT[DM * SEQ];
constexpr int KOFF = 2048 + 16;
constexpr int KSZ = 2112;
constexpr int KCH = 2 * KSZ + 16;

__device__ __forceinline__ void mma_bf16(float (&d)[4], uint32_t a0, uint32_t a1, uint32_t a2, uint32_t a3, uint32_t b0, uint32_t b1) {
  asm volatile("mma.sync.aligned.m16n8k16.row.col.f32.bf16.bf16.f32 {%0,%1,%2,%3}, {%4,%5,%6,%7}, {%8,%9}, {%0,%1,%2,%3};"
               : "+f"(d[0]), "+f"(d[1]), "+f"(d[2]), "+f"(d[3]) : "r"(a0), "r"(a1), "r"(a2), "r"(a3), "r"(b0), "r"(b1));
}
__device__ __forceinline__ void mma_f16(float (&d)[4], uint32_t a0, uint32_t a1, uint32_t a2, uint32_t a3, uint32_t b0, uint32_t b1) {
  asm volatile("mma.sync.aligned.m16n8k16.row.col.f32.f16.f16.f32 {%0,%1,%2,%3}, {%4,%5,%6,%7}, {%8,%9}, {%0,%1,%2,%3};"
               : "+f"(d[0]), "+f"(d[1]), "+f"(d[2]), "+f"(d[3]) : "r"(a0), "r"(a1), "r"(a2), "r"(a3), "r"(b0), "r"(b1));
}
struct cf { float r, i; };
__device__ __forceinline__ cf cmul(cf a, cf b) { cf c; c.r = a.r * b.r - a.i * b.i; c.i = a.r * b.i + a.i * b.r; return c; }
__device__ __forceinline__ cf csq(cf a) { cf c; c.r = a.r * a.r - a.i * a.i; c.i = 2.f * a.r * a.i; return c; }
__device__ __forceinline__ cf cexpp(float ar, float ai, float p) {
  const float e = ex2f(ar * p * 1.4426950408889634f);
  const float th = ai * p;
  const float k = rintf(th * 0.15915494309189535f);
  float r = fmaf(k, -6.2831854820251465f, th);
  r = fmaf(k, 1.7484556000744e-7f, r);
  cf w; w.r = e * __cosf(r); w.i = e * __sinf(r); return w;
}
__device__ __forceinline__ uint32_t packh(float lo, float hi) {
  uint32_t r; asm("cvt.rn.f16x2.f32 %0, %1, %2;" : "=r"(r) : "f"(hi), "f"(lo)); return r;
}

namespace k2 {
constexpr int CH = 8;
constexpr int USEG = 272;
constexpr int USZ = USEG * 9 + 16;
constexpr int TSTR = 40;
constexpr int TABW = 72 * TSTR;
constexpr int P_TAP0 = 0, P_TAPS = 304, P_V2 = 976, P_V4 = 3088, P_V8 = 4752, PAIRW = 6032;
constexpr int OFF_U = 0;
constexpr int OFF_P = OFF_U + CH * USZ * 2;
constexpr int SMEM = OFF_P + CH * PAIRW * 4;
}

__global__ void __launch_bounds__(512, 1)
k2_ssm(const bf16* __restrict__ x, const bf16* __restrict__ logAr, const bf16* __restrict__ Aim, const bf16* __restrict__ Cre,
       const bf16* __restrict__ Cim, const bf16* __restrict__ logdt, const bf16* __restrict__ Dskip,
       const bf16* __restrict__ gatew) {
  using namespace k2;
  extern __shared__ __align__(16) uint8_t sm[];
  const int tid = threadIdx.x, warp = tid >> 5, lane = tid & 31, g = lane >> 2, t = lane & 3;
  const int ch = warp >> 1, half = warp & 1, l64 = half * 32 + lane;
  const int d0 = blockIdx.x * CH;
  bf16* us = reinterpret_cast<bf16*>(sm + OFF_U);
  uint32_t* pw = reinterpret_cast<uint32_t*>(sm + OFF_P) + ch * PAIRW;
  if (tid == 0) TS(2, 0);
  pdl_launch();

  uint4 uv[2][2];
#pragma unroll
  for (int it = 0; it < 2; it++) {
    const int l = 2 * (tid + it * 512);
    uv[it][0] = __ldg(reinterpret_cast<const uint4*>(x + (size_t)l * DM + d0));
    uv[it][1] = __ldg(reinterpret_cast<const uint4*>(x + (size_t)(l + 1) * DM + d0));
  }
  const int d = d0 + ch;
  bf16 p_la[2], p_ai[2], p_cr[2], p_ci[2];
#pragma unroll
  for (int c = 0; c < 2; c++) {
    const int idx = d * NMODE + half * 64 + c * 32 + lane;
    p_la[c] = logAr[idx]; p_ai[c] = Aim[idx]; p_cr[c] = Cre[idx]; p_ci[c] = Cim[idx];
  }
  const bf16 p_dt = logdt[d];
  {
    const int r = blockIdx.x * 16 + warp;
    float s = 0.f;
#pragma unroll
    for (int c = lane * 8; c < DM; c += 256) {
      const uint4 xv = __ldg(reinterpret_cast<const uint4*>(x + (size_t)r * DM + c));
      const uint4 wv = __ldg(reinterpret_cast<const uint4*>(gatew + c));
      const bf16* xp = reinterpret_cast<const bf16*>(&xv);
      const bf16* wp = reinterpret_cast<const bf16*>(&wv);
#pragma unroll
      for (int q = 0; q < 8; q++) s += bfr(__bfloat162float(xp[q]) * __bfloat162float(wp[q]));
    }
#pragma unroll
    for (int o = 16; o; o >>= 1) s += __shfl_xor_sync(0xffffffffu, s, o);
    if (lane == 0) { const float z = bfr(s); g_gate[r] = bfr(1.0f / (1.0f + ex2f(-z * 1.4426950408889634f))); }
  }
  for (int i = tid; i < CH * (USEG / 2 + 8); i += 512) {
    const int c = i / (USEG / 2 + 8), o = i % (USEG / 2 + 8);
    reinterpret_cast<uint32_t*>(us + c * USZ)[o < USEG / 2 ? o : (USEG * 9) / 2 + (o - USEG / 2)] = 0u;
  }
#pragma unroll
  for (int it = 0; it < 2; it++) {
    const int l = 2 * (tid + it * 512);
    const int e = l & 15;
    const int pe = ((e & 7) >> 1) * 4 + (e >> 3) * 2;
    const int pos = USEG * (1 + (l >> 8)) + (l & 240) + pe;
    const uint32_t a[4] = {uv[it][0].x, uv[it][0].y, uv[it][0].z, uv[it][0].w};
    const uint32_t b[4] = {uv[it][1].x, uv[it][1].y, uv[it][1].z, uv[it][1].w};
#pragma unroll
    for (int c = 0; c < 4; c++) {
      *reinterpret_cast<uint32_t*>(us + (2 * c) * USZ + pos) = __byte_perm(a[c], b[c], 0x5410);
      *reinterpret_cast<uint32_t*>(us + (2 * c + 1) * USZ + pos) = __byte_perm(a[c], b[c], 0x7632);
    }
  }

  float acc[5][4];
#pragma unroll
  for (int a = 0; a < 5; a++)
#pragma unroll
    for (int b = 0; b < 4; b++) acc[a][b] = 0.f;
  float last = 0.f, scale;
  {
    const float dt = bfr(ex2f(__bfloat162float(p_dt) * 1.4426950408889634f));
    float cr[2], ci[2], arr[2], aii[2];
#pragma unroll
    for (int c = 0; c < 2; c++) {
      arr[c] = -bfr(ex2f(__bfloat162float(p_la[c]) * 1.4426950408889634f)) * dt;
      aii[c] = __bfloat162float(p_ai[c]) * dt;
      cr[c] = __bfloat162float(p_cr[c]) * dt;
      ci[c] = __bfloat162float(p_ci[c]) * dt;
    }
    float mx = fmaxf(fmaxf(fabsf(cr[0]), fabsf(ci[0])), fmaxf(fabsf(cr[1]), fabsf(ci[1])));
#pragma unroll
    for (int o = 16; o; o >>= 1) mx = fmaxf(mx, __shfl_xor_sync(0xffffffffu, mx, o));
    {
      int e = (int)((__float_as_uint(mx) >> 23) & 255u) + 1;
      e = e < 32 ? 32 : (e > 220 ? 220 : e);
      scale = __uint_as_float((uint32_t)e << 23);
    }
    const float iscale = __uint_as_float((uint32_t)(254 - ((__float_as_uint(scale) >> 23) & 255u)) << 23);
    uint32_t* tab = pw + half * TABW;
#pragma unroll 1
    for (int c = 0; c < 2; c++) {
      const float ar = arr[c], ai = aii[c];
      cf C; C.r = cr[c] * iscale; C.i = ci[c] * iscale;
      const cf W1 = cexpp(ar, ai, 1.f), W16 = cexpp(ar, ai, 16.f), W256 = cexpp(ar, ai, 256.f);
      const cf W512 = csq(W256), W1024 = csq(W512);
      const cf W1536 = cmul(W1024, W512);
      {
        const cf w2048 = csq(W1024);
        last += cr[c] * w2048.r - ci[c] * w2048.i;
      }
      uint32_t* tp = tab + lane;
      {
        cf xa = C;
#pragma unroll
        for (int i = 0; i < 16; i++) {
          tp[i * TSTR] = packh(xa.r, -xa.i);
          if ((i & 1) == 0) {
            tp[(16 + i / 2) * TSTR] = packh(xa.r, -xa.i);
            const cf xb = cmul(xa, W256);
            tp[(24 + i / 2) * TSTR] = packh(xb.r, -xb.i);
          }
          xa = cmul(xa, W16);
        }
      }
      {
        cf y; y.r = 1.f; y.i = 0.f;
        const cf W528 = cmul(W512, W16);
        const cf WA16 = cmul(W1024, W16), WB16 = cmul(W1536, W16);
#pragma unroll
        for (int j = 0; j < 16; j++) {
          tp[(32 + j) * TSTR] = packh(y.r, y.i);
          if ((j & 1) == 0) { const cf z = cmul(y, W256); tp[(48 + j / 2) * TSTR] = packh(z.r, z.i); }
          if ((j & 3) == 0) {
            const cf z0 = cmul(y, W512), z1 = cmul(y, W528);
            tp[(56 + j / 4) * TSTR] = packh(z0.r, z0.i);
            tp[(60 + j / 4) * TSTR] = packh(z1.r, z1.i);
          }
          if ((j & 7) == 0) {
            const cf z0 = cmul(y, W1024), z1 = cmul(y, WA16), z2 = cmul(y, W1536), z3 = cmul(y, WB16);
            tp[(64 + j / 8) * TSTR] = packh(z0.r, z0.i);
            tp[(66 + j / 8) * TSTR] = packh(z1.r, z1.i);
            tp[(68 + j / 8) * TSTR] = packh(z2.r, z2.i);
            tp[(70 + j / 8) * TSTR] = packh(z3.r, z3.i);
          }
          y = cmul(y, W1);
        }
      }
      __syncwarp();
#pragma unroll
      for (int ks4 = 0; ks4 < 4; ks4++) {
        const uint32_t* fp = tab + 8 * ks4 + 2 * t;
        const uint2 xa0 = *reinterpret_cast<const uint2*>(fp + g * TSTR), xa1 = *reinterpret_cast<const uint2*>(fp + (g + 8) * TSTR);
        const uint2 xb0 = *reinterpret_cast<const uint2*>(fp + (16 + g) * TSTR), xb1 = *reinterpret_cast<const uint2*>(fp + (24 + g) * TSTR);
        const uint2 y1 = *reinterpret_cast<const uint2*>(fp + (32 + g) * TSTR), y2 = *reinterpret_cast<const uint2*>(fp + (40 + g) * TSTR);
        const uint2 y3 = *reinterpret_cast<const uint2*>(fp + (48 + g) * TSTR), y4 = *reinterpret_cast<const uint2*>(fp + (56 + g) * TSTR);
        const uint2 y5 = *reinterpret_cast<const uint2*>(fp + (64 + g) * TSTR);
        mma_f16(acc[0], xa0.x, xa1.x, xa0.y, xa1.y, y1.x, y1.y);
        mma_f16(acc[1], xa0.x, xa1.x, xa0.y, xa1.y, y2.x, y2.y);
        mma_f16(acc[2], xa0.x, xa1.x, xa0.y, xa1.y, y3.x, y3.y);
        mma_f16(acc[3], xb0.x, xb1.x, xb0.y, xb1.y, y4.x, y4.y);
        mma_f16(acc[4], xb0.x, xb1.x, xb0.y, xb1.y, y5.x, y5.y);
      }
      __syncwarp();
    }
  }
  if (tid == 0) TS(2, 1);
  __syncthreads();
  float* kqp = reinterpret_cast<float*>(pw + P_V2);
  {
    float* kq = kqp + half * 648;
    const float sc2 = 2.f * scale;
#pragma unroll
    for (int h = 0; h < 2; h++) {
      const int i = g + 8 * h;
      *reinterpret_cast<float2*>(kq + 16 * i + 2 * t) = make_float2(sc2 * acc[0][2 * h], sc2 * acc[0][2 * h + 1]);
      *reinterpret_cast<float2*>(kq + 16 * i + 8 + 2 * t) = make_float2(sc2 * acc[1][2 * h], sc2 * acc[1][2 * h + 1]);
      *reinterpret_cast<float2*>(kq + 256 + 8 * i + 2 * t) = make_float2(sc2 * acc[2][2 * h], sc2 * acc[2][2 * h + 1]);
      *reinterpret_cast<float2*>(kq + 384 + 8 * i + 2 * t) = make_float2(sc2 * acc[3][2 * h], sc2 * acc[3][2 * h + 1]);
      *reinterpret_cast<float2*>(kq + 512 + 4 * i + 64 * (t >> 1) + 2 * (t & 1)) = make_float2(sc2 * acc[4][2 * h], sc2 * acc[4][2 * h + 1]);
    }
#pragma unroll
    for (int o = 16; o; o >>= 1) last += __shfl_xor_sync(0xffffffffu, last, o);
    if (lane == 0) kq[640] = 2.f * last;
  }
  named_bar_sync(1 + ch, 64);
  float k1024b;
  {
    auto KQ = [&](int id) { return kqp[id] + kqp[648 + id]; };
    for (int w = l64; w < 144; w += 64) {
      float v[3];
#pragma unroll
      for (int q = 0; q < 3; q++) {
        const int xx = 272 - 2 * w - q;
        float val = 0.f;
        if (xx >= 0 && xx < 256) { val = KQ(xx); if (xx == 255) val -= bfr(KQ(256)); }
        v[q] = val;
      }
      pw[P_TAP0 + w] = pack2(v[0], v[1]);
      pw[P_TAP0 + 152 + w] = pack2(v[1], v[2]);
    }
    for (int i = l64; i < 6 * 50; i += 64) {
      const int a = i / 50, w = i - a * 50;
      const int base = 128 + (a >> 1) * 128 + (a & 1);
      float v[3];
#pragma unroll
      for (int q = 0; q < 3; q++) {
        const int xx = 144 - 2 * w - q;
        float val = 0.f;
        if (xx >= 64 && (xx < 128 || (xx == 128 && a == 4))) {
          val = KQ(base + 2 * xx);
          if (a == 1 && xx == 127) val -= bfr(KQ(384));
        }
        v[q] = val;
      }
      pw[P_TAPS + a * 112 + w] = pack2(v[0], v[1]);
      pw[P_TAPS + a * 112 + 56 + w] = pack2(v[1], v[2]);
    }
    k1024b = bfr(KQ(512));
  }
  named_bar_sync(1 + ch, 64);
  const bf16* uc = us + ch * USZ;
  if (l64 >= 56 && l64 < 63) {
    for (int i = l64 - 56; i < 8 * 12 + 16 * 6 + 32 * 7; i += 7) {
      int w;
      if (i < 96) { const int r = i % 12; w = P_V2 + (i / 12) * 264 + (r < 8 ? r : 8 + 2 * (r - 8)); }
      else if (i < 192) { const int r = (i - 96) % 6; w = P_V4 + ((i - 96) / 6) * 104 + (r < 5 ? r : 6); }
      else w = P_V8 + ((i - 192) / 7) * 40 + ((i - 192) % 7);
      pw[w] = 0u;
    }
  }
  if (l64 < 56 || l64 == 63) {
    const int t0 = l64 == 63 ? -32 : 32 * l64;
    float P[65];
    P[0] = 0.f;
#pragma unroll
    for (int gi = 0; gi < 4; gi++) {
      const int tg = t0 - 16 + 16 * gi;
      const int ad = tg < 0 ? (tg & 240) : USEG * (1 + (tg >> 8)) + (tg & 240);
      const uint4 v0 = *reinterpret_cast<const uint4*>(uc + ad), v1 = *reinterpret_cast<const uint4*>(uc + ad + 8);
      const uint32_t w[8] = {v0.x, v0.y, v0.z, v0.w, v1.x, v1.y, v1.z, v1.w};
      float e[16];
#pragma unroll
      for (int q = 0; q < 4; q++) {
        e[2 * q] = lo_f(w[2 * q]); e[2 * q + 1] = hi_f(w[2 * q]);
        e[2 * q + 8] = lo_f(w[2 * q + 1]); e[2 * q + 9] = hi_f(w[2 * q + 1]);
      }
      P[16 * gi + 1] = e[0];
#pragma unroll
      for (int q = 1; q < 16; q++) P[16 * gi + q + 1] = P[16 * gi + q] + e[q];
    }
    {
      const float o1 = P[16], o2 = o1 + P[32], o3 = o2 + P[48];
#pragma unroll
      for (int q = 0; q < 16; q++) { P[17 + q] += o1; P[33 + q] += o2; P[49 + q] += o3; }
    }
#define WIN(j, lo, hi) (P[17 + (j) + (hi)] - P[16 + (j) + (lo)])
    {
      const int qq0 = (t0 >> 2) + 32;
      uint32_t* b2 = pw + P_V2 + (qq0 & ~15) / 2 + ((qq0 >> 3) & 1);
#pragma unroll
      for (int rho = 0; rho < 4; rho++)
#pragma unroll
        for (int jp = 0; jp < 4; jp++) {
          const int j0 = 8 * jp + rho, j1 = j0 + 4;
          b2[rho * 264 + 2 * jp] = pack2(WIN(j0, -1, 1), WIN(j1, -1, 1));
          b2[(4 + rho) * 264 + 2 * jp] = pack2(WIN(j0, -2, -2), WIN(j1, -2, -2));
        }
    }
    if (t0 < 1536) {
      const int qq0 = (t0 >> 3) + 16;
      const int e0 = qq0 & 15;
      uint32_t* b4 = pw + P_V4 + (qq0 & ~15) / 2 + 2 * ((e0 & 7) >> 1) + (e0 >> 3);
#pragma unroll
      for (int rho = 0; rho < 8; rho++)
#pragma unroll
        for (int jp = 0; jp < 2; jp++) {
          const int j0 = 16 * jp + rho, j1 = j0 + 8;
          b4[rho * 104 + 2 * jp] = pack2(WIN(j0, -2, 2), WIN(j1, -2, 2));
          b4[(8 + rho) * 104 + 2 * jp] = pack2(WIN(j0, -5, -3), WIN(j1, -5, -3));
        }
    }
    if (t0 < 1024) {
      const int qq0 = (t0 >> 4) + 16;
      const int e0 = qq0 & 15;
      uint32_t* b8 = pw + P_V8 + (qq0 & ~15) / 2 + 2 * ((e0 & 7) >> 1) + (e0 >> 3);
#pragma unroll
      for (int rho = 0; rho < 16; rho++) {
        b8[rho * 40] = pack2(WIN(rho, -4, 4), WIN(rho + 16, -4, 4));
        b8[(16 + rho) * 40] = pack2(WIN(rho, -11, -5), WIN(rho + 16, -11, -5));
      }
    }
#undef WIN
  }
  named_bar_sync(1 + ch, 64);
  if (tid == 0) TS(2, 2);

  float D[16][4];
#pragma unroll
  for (int j = 0; j < 16; j++)
#pragma unroll
    for (int q = 0; q < 4; q++) D[j][q] = 0.f;
  float* y1 = reinterpret_cast<float*>(pw + P_V2);
  if (half == 0) {
    uint32_t F[35];
    const uint32_t* fb = pw + P_TAP0 + ((g & 1) ? 152 : 0) + ((272 - g + 2 * t) >> 1);
#pragma unroll
    for (int m = 0; m < 35; m++) F[m] = fb[-4 * (m - 1)];
    const bf16* ub = uc + USEG * (1 + g) + 4 * t;
#pragma unroll
    for (int k = -16; k < 16; k++) {
      const uint2 b = *reinterpret_cast<const uint2*>(ub + (k < 0 ? 16 * k - 16 : 16 * k));
#pragma unroll
      for (int dl = 0; dl <= 16; dl++) {
        const int i = k + dl;
        if (i >= 0 && i < 16) mma_bf16(D[i], F[2 * dl + 1], F[2 * dl + 2], F[2 * dl], F[2 * dl + 1], b.x, b.y);
      }
    }
  } else {
#pragma unroll
    for (int p = 0; p < 2; p++) {
      uint32_t F[11];
      const uint32_t* fb = pw + P_TAPS + p * 112 + ((g & 1) ? 56 : 0) + ((144 - g + 2 * t) >> 1);
#pragma unroll
      for (int m = 0; m < 11; m++) F[m] = fb[-4 * (m + 7)];
      const uint32_t* vb = pw + P_V2 + (p * 4 + (g & 3)) * 264 + 2 * t;
      const int hh = g >> 2;
#pragma unroll
      for (int k = -8; k < 12; k++) {
        const int tile = k < -2 ? (hh ? k + 18 : 0) : k + 2 + 16 * hh;
        const uint2 b = *reinterpret_cast<const uint2*>(vb + 8 * tile);
#pragma unroll
        for (int dl = 4; dl <= 8; dl++) {
          const int i = k + dl;
          if (i >= 0 && i < 16) mma_bf16(D[i], F[2 * dl - 7], F[2 * dl - 6], F[2 * dl - 8], F[2 * dl - 7], b.x, b.y);
        }
      }
    }
    __syncwarp();
#pragma unroll
    for (int i = 0; i < 16; i++)
#pragma unroll
      for (int q = 0; q < 4; q++) {
        const int n = 2 * t + (q & 1);
        const int l = 4 * (16 * i + g + 8 * (q >> 1)) + 1024 * (n >> 2) + (n & 3);
        y1[l + 4 * (l >> 8)] = D[i][q];
        D[i][q] = 0.f;
      }
#pragma unroll
    for (int p = 0; p < 2; p++) {
      uint32_t F[11];
      const uint32_t* fb = pw + P_TAPS + (2 + p) * 112 + ((g & 1) ? 56 : 0) + ((144 - g + 2 * t) >> 1);
#pragma unroll
      for (int m = 0; m < 11; m++) F[m] = fb[-4 * (m + 7)];
      const uint32_t* vb = pw + P_V4 + (p * 8 + g) * 104 + 2 * t;
#pragma unroll
      for (int k = -1; k < 12; k++) {
        const uint2 b = *reinterpret_cast<const uint2*>(vb + 8 * (k + 1));
#pragma unroll
        for (int dl = 4; dl <= 8; dl++) {
          const int i = k + dl;
          if (i >= 0 && i < 16) mma_bf16(D[i], F[2 * dl - 7], F[2 * dl - 6], F[2 * dl - 8], F[2 * dl - 7], b.x, b.y);
        }
      }
    }
    __syncwarp();
#pragma unroll
    for (int i = 3; i < 16; i++)
#pragma unroll
      for (int q = 0; q < 4; q++) {
        const int l = 8 * (16 * i + g + 8 * (q >> 1)) + 2 * t + (q & 1);
        y1[l + 4 * (l >> 8)] += D[i][q];
        D[i][q] = 0.f;
      }
#pragma unroll
    for (int p = 0; p < 2; p++) {
      uint32_t F[11];
      const uint32_t* fb = pw + P_TAPS + (4 + p) * 112 + ((g & 1) ? 56 : 0) + ((144 - g + 2 * t) >> 1);
#pragma unroll
      for (int m = 0; m < 11; m++) F[m] = fb[-4 * (m + 7)];
#pragma unroll
      for (int nt = 0; nt < 2; nt++) {
        const uint32_t* vb = pw + P_V8 + (p * 16 + nt * 8 + g) * 40 + 2 * t;
#pragma unroll
        for (int k = -1; k < 4; k++) {
          const uint2 b = *reinterpret_cast<const uint2*>(vb + 8 * (k + 1));
#pragma unroll
          for (int dl = 4; dl <= 8; dl++) {
            const int i = k + dl;
            if (i >= 3 && i < 8) mma_bf16(D[2 * (i - 3) + nt], F[2 * dl - 7], F[2 * dl - 6], F[2 * dl - 8], F[2 * dl - 7], b.x, b.y);
          }
        }
      }
    }
    __syncwarp();
#pragma unroll
    for (int i = 3; i < 8; i++)
#pragma unroll
      for (int nt = 0; nt < 2; nt++)
#pragma unroll
        for (int q = 0; q < 4; q++) {
          const int l = 16 * (16 * i + g + 8 * (q >> 1)) + 8 * nt + 2 * t + (q & 1);
          y1[l + 4 * (l >> 8)] += D[2 * (i - 3) + nt][q];
        }
  }
  if (tid == 0) TS(2, 3);
  named_bar_sync(1 + ch, 64);
  float* y0 = reinterpret_cast<float*>(pw + P_V4);
  if (half == 0) {
#pragma unroll
    for (int i = 0; i < 16; i++)
#pragma unroll
      for (int q = 0; q < 4; q++) {
        const int l = 256 * (2 * t + (q & 1)) + 16 * i + g + 8 * (q >> 1);
        y0[l + 4 * (l >> 8)] = D[i][q];
      }
  }
  named_bar_sync(1 + ch, 64);
  {
    const float dsk = __bfloat162float(Dskip[d]);
    bf16* dst = g_bT + (size_t)d * SEQ;
    auto U8 = [&](int tt, float* o) {
      const uint32_t* p = reinterpret_cast<const uint32_t*>(uc + (tt < 0 ? 0 : USEG * (1 + (tt >> 8)) + (tt & 240))) + ((tt >> 3) & 1);
#pragma unroll
      for (int q = 0; q < 4; q++) { const uint32_t w = p[2 * q]; o[2 * q] = lo_f(w); o[2 * q + 1] = hi_f(w); }
    };
#pragma unroll
    for (int it = 0; it < 4; it++) {
      const int l0 = (it * 64 + l64) * 8;
      const int o = l0 + 4 * (l0 >> 8);
      const float4 a0 = *reinterpret_cast<const float4*>(y0 + o), a1 = *reinterpret_cast<const float4*>(y0 + o + 4);
      const float4 c0 = *reinterpret_cast<const float4*>(y1 + o), c1 = *reinterpret_cast<const float4*>(y1 + o + 4);
      float y[8] = {a0.x + c0.x, a0.y + c0.y, a0.z + c0.z, a0.w + c0.w, a1.x + c1.x, a1.y + c1.y, a1.z + c1.z, a1.w + c1.w};
      float ul[8];
      U8(l0, ul);
      if (it >= 1 && l0 >= 1016) {
        float ua[16];
        U8(l0 - 1024, ua); U8(l0 - 1016, ua + 8);
#pragma unroll
        for (int q = 0; q < 8; q++) y[q] -= k1024b * (ua[q + 4] + ua[q + 3]);
      }
      uint32_t ow[4];
#pragma unroll
      for (int q = 0; q < 4; q++)
        ow[q] = pack2(bfr(y[2 * q]) + bfr(ul[2 * q] * dsk), bfr(y[2 * q + 1]) + bfr(ul[2 * q + 1] * dsk));
      *reinterpret_cast<uint4*>(dst + l0) = make_uint4(ow[0], ow[1], ow[2], ow[3]);
    }
  }
  if (tid == 0) TS(2, 4);
}

typedef CUresult (*EncodeFn)(CUtensorMap*, CUtensorMapDataType, cuuint32_t, void*, const cuuint64_t*, const cuuint64_t*,
                             const cuuint32_t*, const cuuint32_t*, CUtensorMapInterleave, CUtensorMapSwizzle,
                             CUtensorMapL2promotion, CUtensorMapFloatOOBfill);

static void make_map(EncodeFn enc, CUtensorMap* m, void* ptr, uint64_t inner, uint64_t outer, uint32_t bi, uint32_t bo) {
  cuuint64_t dims[2] = {inner, outer};
  cuuint64_t strides[1] = {inner * 2};
  cuuint32_t box[2] = {bi, bo};
  cuuint32_t es[2] = {1, 1};
  enc(m, CU_TENSOR_MAP_DATA_TYPE_BFLOAT16, 2, ptr, dims, strides, box, es, CU_TENSOR_MAP_INTERLEAVE_NONE,
      CU_TENSOR_MAP_SWIZZLE_128B, CU_TENSOR_MAP_L2_PROMOTION_L2_256B, CU_TENSOR_MAP_FLOAT_OOB_FILL_NONE);
}

extern "C" void kernel_launch(void* const* d_in, const int* in_sizes, int n_in, void* d_out, int out_size) {
  const bf16* x = (const bf16*)d_in[0];
  const bf16* wqkv = (const bf16*)d_in[1];
  const bf16* wo = (const bf16*)d_in[2];
  const bf16* logAr = (const bf16*)d_in[4];
  const bf16* Aim = (const bf16*)d_in[5];
  const bf16* Cre = (const bf16*)d_in[6];
  const bf16* Cim = (const bf16*)d_in[7];
  const bf16* logdt = (const bf16*)d_in[8];
  const bf16* Dskip = (const bf16*)d_in[9];
  const bf16* gatew = (const bf16*)d_in[10];

  static EncodeFn enc = nullptr;
  static void* p_o = nullptr;
  static void* p_bT = nullptr;
  if (!enc) {
    void* fn = nullptr;
    cudaDriverEntryPointQueryResult qr;
    cudaGetDriverEntryPoint("cuTensorMapEncodeTiled", &fn, cudaEnableDefault, &qr);
    enc = (EncodeFn)fn;
    cudaGetSymbolAddress(&p_o, g_o);
    cudaGetSymbolAddress(&p_bT, g_bT);
    cudaFuncSetAttribute(k1_qkv_attn, cudaFuncAttributeMaxDynamicSharedMemorySize, k1::SMEM);
    cudaFuncSetAttribute(k2_ssm, cudaFuncAttributeMaxDynamicSharedMemorySize, k2::SMEM);
    cudaFuncSetAttribute(k3_out, cudaFuncAttributeMaxDynamicSharedMemorySize, k3::SMEM);
  }
  CUtensorMap tmx, tmw, tmo, tmwo, tmbt, tmout;
  make_map(enc, &tmx, (void*)x, 1024, 2048, 64, 128);
  make_map(enc, &tmw, (void*)wqkv, 3072, 1024, 64, 64);
  make_map(enc, &tmo, p_o, 1024, 2048, 64, 64);
  make_map(enc, &tmwo, (void*)wo, 1024, 1024, 64, 64);
  make_map(enc, &tmbt, p_bT, 2048, 1024, 64, 128);
  make_map(enc, &tmout, d_out, 1024, 2048, 64, 64);

  k2_ssm<<<128, 512, k2::SMEM>>>(x, logAr, Aim, Cre, Cim, logdt, Dskip, gatew);
  cudaLaunchAttribute at[1];
  at[0].id = cudaLaunchAttributeProgrammaticStreamSerialization;
  at[0].val.programmaticStreamSerializationAllowed = 1;
  cudaLaunchConfig_t cfg = {};
  cfg.gridDim = dim3(128); cfg.blockDim = dim3(384); cfg.stream = cudaStreamPerThread; cfg.attrs = at; cfg.numAttrs = 1;
  cfg.dynamicSmemBytes = k1::SMEM;
  cudaLaunchKernelEx(&cfg, k1_qkv_attn, tmx, tmw);
  cfg.dynamicSmemBytes = k3::SMEM;
  cudaLaunchKernelEx(&cfg, k3_out, tmo, tmwo, tmbt, tmout);
}
```

```cpp
#include <cuda_runtime.h>
#include <cuda_bf16.h>
#include <cuda.h>
#include <stdint.h>

typedef __nv_bfloat16 bf16;

constexpr int SEQ = 2048, DM = 1024, NMODE = 128;

__device__ __align__(1024) bf16 g_o[SEQ * DM];
__device__ __align__(1024) bf16 g_b[SEQ * DM];
__device__ float g_gate[SEQ];
__device__ __align__(16) float g_part[16 * 8 * 2 * 1056];
__device__ unsigned int g_cnt[16];

#define TS(k, i) do {} while (0)
__device__ __forceinline__ uint32_t smem_u32(const void* p) { return (uint32_t)__cvta_generic_to_shared(p); }
__device__ __forceinline__ void mbar_init(uint32_t bar, uint32_t cnt) {
  asm volatile("mbarrier.init.shared::cta.b64 [%0], %1;" ::"r"(bar), "r"(cnt));
}
__device__ __forceinline__ void mbar_expect_tx(uint32_t bar, uint32_t bytes) {
  asm volatile("mbarrier.arrive.expect_tx.shared::cta.b64 _, [%0], %1;" ::"r"(bar), "r"(bytes) : "memory");
}
__device__ __forceinline__ void mbar_arrive_cluster(uint32_t bar, uint32_t cta) {
  asm volatile(
      "{\n.reg .b32 ra;\nmapa.shared::cluster.u32 ra, %0, %1;\n"
      "mbarrier.arrive.shared::cluster.b64 _, [ra];\n}\n" ::"r"(bar), "r"(cta) : "memory");
}
__device__ __forceinline__ bool mbar_try_wait(uint32_t bar, uint32_t parity) {
  uint32_t ok;
  asm volatile(
      "{\n.reg .pred p;\nmbarrier.try_wait.parity.shared::cta.b64 p, [%1], %2;\nselp.u32 %0, 1, 0, p;\n}\n"
      : "=r"(ok) : "r"(bar), "r"(parity) : "memory");
  return ok;
}
__device__ __forceinline__ void mbar_wait(uint32_t bar, uint32_t parity) {
  while (!mbar_try_wait(bar, parity)) {}
}
__device__ __forceinline__ void tma_load_2d(uint32_t dst, const CUtensorMap* map, uint32_t bar, int c0, int c1) {
  asm volatile(
      "cp.async.bulk.tensor.2d.shared::cluster.global.mbarrier::complete_tx::bytes [%0], [%1, {%3, %4}], [%2];" ::"r"(dst),
      "l"(map), "r"(bar), "r"(c0), "r"(c1) : "memory");
}
__device__ __forceinline__ void tma_load_2d_mc(uint32_t dst, const CUtensorMap* map, uint32_t bar, int c0, int c1,
                                               uint16_t mask) {
  asm volatile(
      "cp.async.bulk.tensor.2d.shared::cluster.global.mbarrier::complete_tx::bytes.multicast::cluster [%0], [%1, {%3, %4}], [%2], %5;" ::"r"(dst),
      "l"(map), "r"(bar), "r"(c0), "r"(c1), "h"(mask) : "memory");
}
__device__ __forceinline__ void cluster_sync_all() {
  asm volatile("barrier.cluster.arrive.release.aligned;\nbarrier.cluster.wait.acquire.aligned;\n" ::: "memory");
}
__device__ __forceinline__ uint32_t cluster_ctarank() {
  uint32_t r; asm volatile("mov.u32 %0, %%cluster_ctarank;" : "=r"(r)); return r;
}
__device__ __forceinline__ void pdl_wait() { asm volatile("griddepcontrol.wait;" ::: "memory"); }
__device__ __forceinline__ void pdl_launch() { asm volatile("griddepcontrol.launch_dependents;" ::: "memory"); }
__device__ __forceinline__ void named_bar_sync(int id, int n) { asm volatile("bar.sync %0, %1;" ::"r"(id), "r"(n) : "memory"); }
__device__ __forceinline__ void fence_async_smem() { asm volatile("fence.proxy.async.shared::cta;" ::: "memory"); }
__device__ __forceinline__ void wg_fence() { asm volatile("wgmma.fence.sync.aligned;" ::: "memory"); }
__device__ __forceinline__ void wg_commit() { asm volatile("wgmma.commit_group.sync.aligned;" ::: "memory"); }
template <int N> __device__ __forceinline__ void wg_wait() { asm volatile("wgmma.wait_group.sync.aligned %0;" ::"n"(N) : "memory"); }
__device__ __forceinline__ uint64_t make_desc(uint32_t addr, uint32_t lbo, uint32_t sbo) {
  return (uint64_t)((addr & 0x3FFFF) >> 4) | ((uint64_t)(lbo >> 4) << 16) | ((uint64_t)(sbo >> 4) << 32) | (1ull << 62);
}
__device__ __forceinline__ float bfr(float x) { return __bfloat162float(__float2bfloat16_rn(x)); }
__device__ __forceinline__ uint32_t pack2(float lo, float hi) {
  __nv_bfloat162 v = __floats2bfloat162_rn(lo, hi);
  return *reinterpret_cast<uint32_t*>(&v);
}
__device__ __forceinline__ float ex2f(float x) { float r; asm("ex2.approx.ftz.f32 %0, %1;" : "=f"(r) : "f"(x)); return r; }
__device__ __forceinline__ float lo_f(uint32_t v) { return __uint_as_float(v << 16); }
__device__ __forceinline__ float hi_f(uint32_t v) { return __uint_as_float(v & 0xffff0000u); }
__device__ __forceinline__ uint32_t phi2(float a0, float a1) {
  const uint32_t t2 = pack2(a0, a1);
  const float t0 = lo_f(t2), t1 = hi_f(t2);
  const float e0 = ex2f(t0 * 1.4426950408889634f), e1 = ex2f(t1 * 1.4426950408889634f);
  const float f0 = t0 > 0.f ? t0 + 1.0f : e0;
  const float f1 = t1 > 0.f ? t1 + 1.0f : e1;
  const uint32_t f2 = pack2(f0, f1);
  return pack2(lo_f(f2) + 1e-6f, hi_f(f2) + 1e-6f);
}
template <int R> __device__ __forceinline__ void fence_regs(float (&d)[R]) {
#pragma unroll
  for (int i = 0; i < R; i++) asm volatile("" : "+f"(d[i])::"memory");
}

__device__ __forceinline__ void wgmma_ss_n192_tb(float (&d)[96], uint64_t da, uint64_t db, int sc) {
  asm volatile("{\n.reg .pred p;\nsetp.ne.b32 p, %98, 0;\n"
    "wgmma.mma_async.sync.aligned.m64n192k16.f32.bf16.bf16 {%0, %1, %2, %3, %4, %5, %6, %7, %8, %9, %10, %11, %12, %13, %14, %15, %16, %17, %18, %19, %20, %21, %22, %23, %24, %25, %26, %27, %28, %29, %30, %31, %32, %33, %34, %35, %36, %37, %38, %39, %40, %41, %42, %43, %44, %45, %46, %47, %48, %49, %50, %51, %52, %53, %54, %55, %56, %57, %58, %59, %60, %61, %62, %63, %64, %65, %66, %67, %68, %69, %70, %71, %72, %73, %74, %75, %76, %77, %78, %79, %80, %81, %82, %83, %84, %85, %86, %87, %88, %89, %90, %91, %92, %93, %94, %95}, %96, %97, p, 1, 1, 0, 1;\n}\n"
    : "+f"(d[0]), "+f"(d[1]), "+f"(d[2]), "+f"(d[3]), "+f"(d[4]), "+f"(d[5]), "+f"(d[6]), "+f"(d[7]), "+f"(d[8]), "+f"(d[9]), "+f"(d[10]), "+f"(d[11]), "+f"(d[12]), "+f"(d[13]), "+f"(d[14]), "+f"(d[15]), "+f"(d[16]), "+f"(d[17]), "+f"(d[18]), "+f"(d[19]), "+f"(d[20]), "+f"(d[21]), "+f"(d[22]), "+f"(d[23]), "+f"(d[24]), "+f"(d[25]), "+f"(d[26]), "+f"(d[27]), "+f"(d[28]), "+f"(d[29]), "+f"(d[30]), "+f"(d[31]), "+f"(d[32]), "+f"(d[33]), "+f"(d[34]), "+f"(d[35]), "+f"(d[36]), "+f"(d[37]), "+f"(d[38]), "+f"(d[39]), "+f"(d[40]), "+f"(d[41]), "+f"(d[42]), "+f"(d[43]), "+f"(d[44]), "+f"(d[45]), "+f"(d[46]), "+f"(d[47]), "+f"(d[48]), "+f"(d[49]), "+f"(d[50]), "+f"(d[51]), "+f"(d[52]), "+f"(d[53]), "+f"(d[54]), "+f"(d[55]), "+f"(d[56]), "+f"(d[57]), "+f"(d[58]), "+f"(d[59]), "+f"(d[60]), "+f"(d[61]), "+f"(d[62]), "+f"(d[63]), "+f"(d[64]), "+f"(d[65]), "+f"(d[66]), "+f"(d[67]), "+f"(d[68]), "+f"(d[69]), "+f"(d[70]), "+f"(d[71]), "+f"(d[72]), "+f"(d[73]), "+f"(d[74]), "+f"(d[75]), "+f"(d[76]), "+f"(d[77]), "+f"(d[78]), "+f"(d[79]), "+f"(d[80]), "+f"(d[81]), "+f"(d[82]), "+f"(d[83]), "+f"(d[84]), "+f"(d[85]), "+f"(d[86]), "+f"(d[87]), "+f"(d[88]), "+f"(d[89]), "+f"(d[90]), "+f"(d[91]), "+f"(d[92]), "+f"(d[93]), "+f"(d[94]), "+f"(d[95])
    : "l"(da), "l"(db), "r"(sc));
}

__device__ __forceinline__ void wgmma_ss_n128_tb(float (&d)[64], uint64_t da, uint64_t db, int sc) {
  asm volatile("{\n.reg .pred p;\nsetp.ne.b32 p, %66, 0;\n"
    "wgmma.mma_async.sync.aligned.m64n128k16.f32.bf16.bf16 {%0, %1, %2, %3, %4, %5, %6, %7, %8, %9, %10, %11, %12, %13, %14, %15, %16, %17, %18, %19, %20, %21, %22, %23, %24, %25, %26, %27, %28, %29, %30, %31, %32, %33, %34, %35, %36, %37, %38, %39, %40, %41, %42, %43, %44, %45, %46, %47, %48, %49, %50, %51, %52, %53, %54, %55, %56, %57, %58, %59, %60, %61, %62, %63}, %64, %65, p, 1, 1, 0, 1;\n}\n"
    : "+f"(d[0]), "+f"(d[1]), "+f"(d[2]), "+f"(d[3]), "+f"(d[4]), "+f"(d[5]), "+f"(d[6]), "+f"(d[7]), "+f"(d[8]), "+f"(d[9]), "+f"(d[10]), "+f"(d[11]), "+f"(d[12]), "+f"(d[13]), "+f"(d[14]), "+f"(d[15]), "+f"(d[16]), "+f"(d[17]), "+f"(d[18]), "+f"(d[19]), "+f"(d[20]), "+f"(d[21]), "+f"(d[22]), "+f"(d[23]), "+f"(d[24]), "+f"(d[25]), "+f"(d[26]), "+f"(d[27]), "+f"(d[28]), "+f"(d[29]), "+f"(d[30]), "+f"(d[31]), "+f"(d[32]), "+f"(d[33]), "+f"(d[34]), "+f"(d[35]), "+f"(d[36]), "+f"(d[37]), "+f"(d[38]), "+f"(d[39]), "+f"(d[40]), "+f"(d[41]), "+f"(d[42]), "+f"(d[43]), "+f"(d[44]), "+f"(d[45]), "+f"(d[46]), "+f"(d[47]), "+f"(d[48]), "+f"(d[49]), "+f"(d[50]), "+f"(d[51]), "+f"(d[52]), "+f"(d[53]), "+f"(d[54]), "+f"(d[55]), "+f"(d[56]), "+f"(d[57]), "+f"(d[58]), "+f"(d[59]), "+f"(d[60]), "+f"(d[61]), "+f"(d[62]), "+f"(d[63])
    : "l"(da), "l"(db), "r"(sc));
}

__device__ __forceinline__ void wgmma_ss_n64_tatb(float (&d)[32], uint64_t da, uint64_t db, int sc) {
  asm volatile("{\n.reg .pred p;\nsetp.ne.b32 p, %34, 0;\n"
    "wgmma.mma_async.sync.aligned.m64n64k16.f32.bf16.bf16 {%0, %1, %2, %3, %4, %5, %6, %7, %8, %9, %10, %11, %12, %13, %14, %15, %16, %17, %18, %19, %20, %21, %22, %23, %24, %25, %26, %27, %28, %29, %30, %31}, %32, %33, p, 1, 1, 1, 1;\n}\n"
    : "+f"(d[0]), "+f"(d[1]), "+f"(d[2]), "+f"(d[3]), "+f"(d[4]), "+f"(d[5]), "+f"(d[6]), "+f"(d[7]), "+f"(d[8]), "+f"(d[9]), "+f"(d[10]), "+f"(d[11]), "+f"(d[12]), "+f"(d[13]), "+f"(d[14]), "+f"(d[15]), "+f"(d[16]), "+f"(d[17]), "+f"(d[18]), "+f"(d[19]), "+f"(d[20]), "+f"(d[21]), "+f"(d[22]), "+f"(d[23]), "+f"(d[24]), "+f"(d[25]), "+f"(d[26]), "+f"(d[27]), "+f"(d[28]), "+f"(d[29]), "+f"(d[30]), "+f"(d[31])
    : "l"(da), "l"(db), "r"(sc));
}

__device__ __forceinline__ void wgmma_ss_n8_tatb(float (&d)[4], uint64_t da, uint64_t db, int sc) {
  asm volatile("{\n.reg .pred p;\nsetp.ne.b32 p, %6, 0;\n"
    "wgmma.mma_async.sync.aligned.m64n8k16.f32.bf16.bf16 {%0, %1, %2, %3}, %4, %5, p, 1, 1, 1, 1;\n}\n"
    : "+f"(d[0]), "+f"(d[1]), "+f"(d[2]), "+f"(d[3])
    : "l"(da), "l"(db), "r"(sc));
}

__device__ __forceinline__ void wgmma_rs_n40_tb(float (&d)[20], uint32_t a0, uint32_t a1, uint32_t a2, uint32_t a3, uint64_t db, int sc) {
  asm volatile("{\n.reg .pred p;\nsetp.ne.b32 p, %25, 0;\n"
    "wgmma.mma_async.sync.aligned.m64n40k16.f32.bf16.bf16 {%0, %1, %2, %3, %4, %5, %6, %7, %8, %9, %10, %11, %12, %13, %14, %15, %16, %17, %18, %19}, {%20, %21, %22, %23}, %24, p, 1, 1, 1;\n}\n"
    : "+f"(d[0]), "+f"(d[1]), "+f"(d[2]), "+f"(d[3]), "+f"(d[4]), "+f"(d[5]), "+f"(d[6]), "+f"(d[7]), "+f"(d[8]), "+f"(d[9]), "+f"(d[10]), "+f"(d[11]), "+f"(d[12]), "+f"(d[13]), "+f"(d[14]), "+f"(d[15]), "+f"(d[16]), "+f"(d[17]), "+f"(d[18]), "+f"(d[19])
    : "r"(a0), "r"(a1), "r"(a2), "r"(a3), "l"(db), "r"(sc));
}

namespace k1 {
constexpr int BM = 256, BN = 192, BK = 64, ST = 4;
constexpr int A_BYTES = BM * BK * 2, B_BYTES = BK * BN * 2, STAGE = A_BYTES + B_BYTES;
constexpr int SMEM = ST * STAGE + 1024 + 256;
constexpr int OFF_PK = 0, OFF_V = 32768, OFF_ONES = 65536, OFF_KV = 69632, OFF_O = 81920, OFF_RED = 114688;
}

__global__ void __cluster_dims__(2, 1, 1) __launch_bounds__(384, 1)
k1_qkv_attn(const __grid_constant__ CUtensorMap tmx, const __grid_constant__ CUtensorMap tmw,
            const bf16* __restrict__ x, const bf16* __restrict__ gatew) {
  using namespace k1;
  extern __shared__ uint8_t smem_raw[];
  const uint32_t sbase = (smem_u32(smem_raw) + 1023) & ~1023u;
  uint8_t* sgen = smem_raw + (sbase - smem_u32(smem_raw));
  const uint32_t bars = sbase + ST * STAGE;
  const int tid = threadIdx.x, warp = tid >> 5, lane = tid & 31;
  const uint32_t rank = cluster_ctarank();
  const int cl = blockIdx.x >> 1;
  const int mt = cl >> 3;
  const int hp = ((cl & 7) << 1) + rank;
  const int m0 = mt * BM;

  if (tid == 0) {
    for (int s = 0; s < ST; s++) {
      mbar_init(bars + 8 * s, 1);
      mbar_init(bars + 8 * (ST + s), 16);
    }
    asm volatile("fence.mbarrier_init.release.cluster;" ::: "memory");
  }
  cluster_sync_all();
  pdl_launch();

  if (warp >= 8) {
    asm volatile("setmaxnreg.dec.sync.aligned.u32 40;");
    if (warp == 8 && lane == 0) {
      for (int kb = 0; kb < DM / BK; kb++) {
        const int s = kb % ST;
        mbar_wait(bars + 8 * (ST + s), ((kb / ST) & 1) ^ 1);
        const uint32_t full = bars + 8 * s;
        mbar_expect_tx(full, STAGE);
        const uint32_t sa = sbase + s * STAGE, sb = sa + A_BYTES;
        tma_load_2d_mc(sa + rank * 16384, &tmx, full, kb * BK, m0 + rank * 128, (uint16_t)3);
#pragma unroll
        for (int j = 0; j < 3; j++) tma_load_2d(sb + j * 8192, &tmw, full, j * 1024 + hp * 64, kb * BK);
      }
      pdl_wait();
    } else if (warp > 8) {
      for (int rr = warp - 9; rr < 16; rr += 3) {
        const int r = blockIdx.x * 16 + rr;
        float s = 0.f;
#pragma unroll
        for (int c = lane * 8; c < DM; c += 256) {
          const uint4 xv = __ldg(reinterpret_cast<const uint4*>(x + (size_t)r * DM + c));
          const uint4 wv = __ldg(reinterpret_cast<const uint4*>(gatew + c));
          const bf16* xp = reinterpret_cast<const bf16*>(&xv);
          const bf16* wp = reinterpret_cast<const bf16*>(&wv);
#pragma unroll
          for (int q = 0; q < 8; q++) s += bfr(__bfloat162float(xp[q]) * __bfloat162float(wp[q]));
        }
#pragma unroll
        for (int o = 16; o; o >>= 1) s += __shfl_xor_sync(0xffffffffu, s, o);
        if (lane == 0) { const float z = bfr(s); g_gate[r] = bfr(1.0f / (1.0f + ex2f(-z * 1.4426950408889634f))); }
      }
    }
    __syncwarp();
    cluster_sync_all();
  } else {
    asm volatile("setmaxnreg.inc.sync.aligned.u32 232;");
    const int wg = warp >> 2, w4 = warp & 3, g = lane >> 2, t = lane & 3;
    if (tid == 0) TS(1, 0);
    float acc[2][96];
#pragma unroll
    for (int i = 0; i < 96; i++) { acc[0][i] = 0.f; acc[1][i] = 0.f; }
    for (int kb = 0; kb < DM / BK; kb++) {
      const int s = kb % ST;
      mbar_wait(bars + 8 * s, (kb / ST) & 1);
      const uint32_t sa = sbase + s * STAGE + wg * 16384, sb = sbase + s * STAGE + A_BYTES;
      wg_fence();
#pragma unroll
      for (int ks = 0; ks < 4; ks++) {
        const uint64_t db = make_desc(sb + ks * 2048, 8192, 1024);
#pragma unroll
        for (int mb = 0; mb < 2; mb++) {
          const uint64_t da = make_desc(sa + mb * 8192 + ks * 32, 16, 1024);
          wgmma_ss_n192_tb(acc[mb], da, db, 1);
        }
      }
      wg_commit();
      if (kb > 0) {
        wg_wait<1>();
        const int sp = (kb - 1) % ST;
        if (lane == 0) { mbar_arrive_cluster(bars + 8 * (ST + sp), 0); mbar_arrive_cluster(bars + 8 * (ST + sp), 1); }
      }
    }
    wg_wait<0>();
    fence_regs(acc[0]); fence_regs(acc[1]);
    if (tid == 0) TS(1, 1);
    named_bar_sync(1, 256);

#pragma unroll
    for (int mb = 0; mb < 2; mb++) {
#pragma unroll
      for (int h = 0; h < 2; h++) {
        const int r = wg * 128 + mb * 64 + w4 * 16 + g + h * 8;
#pragma unroll
        for (int j = 0; j < 8; j++) {
          const uint32_t off = r * 128 + ((j ^ (r & 7)) << 4) + t * 4;
          const float k0 = acc[mb][4 * (8 + j) + 2 * h], k1v = acc[mb][4 * (8 + j) + 2 * h + 1];
          const float v0 = acc[mb][4 * (16 + j) + 2 * h], v1 = acc[mb][4 * (16 + j) + 2 * h + 1];
          *reinterpret_cast<uint32_t*>(sgen + OFF_PK + off) = phi2(k0, k1v);
          *reinterpret_cast<uint32_t*>(sgen + OFF_V + off) = pack2(v0, v1);
        }
      }
    }
    if (tid < 256) *reinterpret_cast<uint32_t*>(sgen + OFF_ONES + tid * 4) = 0x3F803F80u;
    fence_async_smem();
    named_bar_sync(1, 256);

    if (tid == 0) TS(1, 2);
    float* part = g_part + (size_t)(hp * 8 + mt) * 2112;
    {
      float kv[32], zz[4];
#pragma unroll
      for (int i = 0; i < 32; i++) kv[i] = 0.f;
#pragma unroll
      for (int i = 0; i < 4; i++) zz[i] = 0.f;
      wg_fence();
#pragma unroll
      for (int ks = 0; ks < 8; ks++) {
        const uint64_t da = make_desc(sbase + OFF_PK + wg * 16384 + ks * 2048, 16, 1024);
        const uint64_t db = make_desc(sbase + OFF_V + wg * 16384 + ks * 2048, 16, 1024);
        const uint64_t d1 = make_desc(sbase + OFF_ONES, 16, 0);
        wgmma_ss_n64_tatb(kv, da, db, 1);
        wgmma_ss_n8_tatb(zz, da, d1, 1);
      }
      wg_commit();
      wg_wait<0>();
      fence_regs(kv); fence_regs(zz);
      const int hh = w4 >> 1;
      float* red = reinterpret_cast<float*>(sgen + OFF_RED);
      float vals[2][4][2];
#pragma unroll
      for (int h = 0; h < 2; h++)
#pragma unroll
        for (int j = 0; j < 4; j++) {
          vals[h][j][0] = hh ? kv[4 * (4 + j) + 2 * h] : kv[4 * j + 2 * h];
          vals[h][j][1] = hh ? kv[4 * (4 + j) + 2 * h + 1] : kv[4 * j + 2 * h + 1];
        }
      if (wg == 1) {
#pragma unroll
        for (int h = 0; h < 2; h++) {
          const int d = (w4 & 1) * 16 + g + h * 8;
#pragma unroll
          for (int j = 0; j < 4; j++)
            *reinterpret_cast<float2*>(red + hh * 1056 + d * 32 + 8 * j + 2 * t) = make_float2(vals[h][j][0], vals[h][j][1]);
          if (t == 0) red[hh * 1056 + 1024 + d] = zz[2 * h];
        }
      }
      named_bar_sync(1, 256);
      if (wg == 0) {
#pragma unroll
        for (int h = 0; h < 2; h++) {
          const int d = (w4 & 1) * 16 + g + h * 8;
#pragma unroll
          for (int j = 0; j < 4; j++) {
            const float2 o = *reinterpret_cast<const float2*>(red + hh * 1056 + d * 32 + 8 * j + 2 * t);
            *reinterpret_cast<float2*>(part + hh * 1056 + d * 32 + 8 * j + 2 * t) = make_float2(vals[h][j][0] + o.x, vals[h][j][1] + o.y);
          }
          if (t == 0) part[hh * 1056 + 1024 + d] = zz[2 * h] + red[hh * 1056 + 1024 + d];
        }
        __threadfence();
        named_bar_sync(2, 128);
        if (tid == 0) atomicAdd(&g_cnt[hp], 1u);
      }
    }
    if (tid == 0) TS(1, 3);
    uint32_t pq[2][4][4];
#pragma unroll
    for (int mb = 0; mb < 2; mb++)
#pragma unroll
      for (int kk = 0; kk < 4; kk++) {
        pq[mb][kk][0] = phi2(acc[mb][8 * kk + 0], acc[mb][8 * kk + 1]);
        pq[mb][kk][1] = phi2(acc[mb][8 * kk + 2], acc[mb][8 * kk + 3]);
        pq[mb][kk][2] = phi2(acc[mb][8 * kk + 4], acc[mb][8 * kk + 5]);
        pq[mb][kk][3] = phi2(acc[mb][8 * kk + 6], acc[mb][8 * kk + 7]);
      }
    if (tid == 0) TS(1, 4);
    if (tid == 0) {
      unsigned int v;
      do { asm volatile("ld.acquire.gpu.global.u32 %0, [%1];" : "=r"(v) : "l"(&g_cnt[hp]) : "memory"); } while (v < 8u);
    }
    named_bar_sync(1, 256);
    {
      if (tid == 0) TS(1, 5);
      const float* pb = g_part + (size_t)(hp * 8) * 2112;
      for (int i = tid; i < 528; i += 256) {
        float4 s4 = make_float4(0.f, 0.f, 0.f, 0.f);
#pragma unroll
        for (int p = 0; p < 8; p++) {
          float4 v4 = __ldcg(reinterpret_cast<const float4*>(pb + p * 2112) + i);
          s4.x += v4.x; s4.y += v4.y; s4.z += v4.z; s4.w += v4.w;
        }
        const int hh = i / 264, rem = i - hh * 264;
        uint8_t* tile = sgen + OFF_KV + hh * 4096;
        if (rem < 256) {
          const int d = rem >> 3, e = (rem & 7) * 4;
          const uint32_t off = d * 128 + (((e >> 3) ^ (d & 7)) << 4) + (e & 7) * 2;
          *reinterpret_cast<uint2*>(tile + off) = make_uint2(pack2(s4.x, s4.y), pack2(s4.z, s4.w));
        } else {
          const int d0 = (rem - 256) * 4;
          float zv[4] = {s4.x, s4.y, s4.z, s4.w};
#pragma unroll
          for (int q = 0; q < 4; q++) {
            const int d = d0 + q;
            const uint32_t off = d * 128 + ((4 ^ (d & 7)) << 4);
            *reinterpret_cast<uint4*>(tile + off) = make_uint4(pack2(zv[q], 0.f), 0u, 0u, 0u);
          }
        }
      }
    }
    fence_async_smem();
    named_bar_sync(1, 256);
    if (tid == 0) TS(1, 6);
#pragma unroll
    for (int mb = 0; mb < 2; mb++) {
#pragma unroll
      for (int hh = 0; hh < 2; hh++) {
        float num[20];
#pragma unroll
        for (int i = 0; i < 20; i++) num[i] = 0.f;
        wg_fence();
#pragma unroll
        for (int kk = 0; kk < 2; kk++) {
          const uint64_t db = make_desc(sbase + OFF_KV + hh * 4096 + kk * 2048, 16, 1024);
          wgmma_rs_n40_tb(num, pq[mb][hh * 2 + kk][0], pq[mb][hh * 2 + kk][1], pq[mb][hh * 2 + kk][2], pq[mb][hh * 2 + kk][3], db, 1);
        }
        wg_commit();
        wg_wait<0>();
        fence_regs(num);
#pragma unroll
        for (int h = 0; h < 2; h++) {
          float den = __shfl_sync(0xffffffffu, num[16 + 2 * h], lane & ~3);
          den = bfr(bfr(den) + 1e-6f);
          const float rden = 1.0f / den;
          const int r = wg * 128 + mb * 64 + w4 * 16 + g + h * 8;
#pragma unroll
          for (int j = 0; j < 4; j++) {
            const uint32_t n2 = pack2(num[4 * j + 2 * h], num[4 * j + 2 * h + 1]);
            const float o0 = lo_f(n2) * rden, o1 = hi_f(n2) * rden;
            const uint32_t off = r * 128 + (((hh * 4 + j) ^ (r & 7)) << 4) + t * 4;
            *reinterpret_cast<uint32_t*>(sgen + OFF_O + off) = pack2(o0, o1);
          }
        }
      }
    }
    named_bar_sync(1, 256);
    if (tid == 0) TS(1, 7);
    for (int i = tid; i < 256 * 8; i += 256) {
      const int r = i >> 3, c = i & 7;
      uint4 v = *reinterpret_cast<const uint4*>(sgen + OFF_O + r * 128 + ((c ^ (r & 7)) << 4));
      *reinterpret_cast<uint4*>(g_o + (size_t)(m0 + r) * DM + hp * 64 + c * 8) = v;
    }
    if (tid == 0) TS(1, 8);
    cluster_sync_all();
  }
}

namespace k3 {
constexpr int BM = 128, BN = 128, BK = 64, ST = 5;
constexpr int A_BYTES = BM * BK * 2, B_BYTES = BK * BN * 2, STAGE = A_BYTES + B_BYTES;
constexpr int OFF_BT = ST * STAGE;
constexpr int OFF_BAR = OFF_BT + 32768;
constexpr int SMEM = OFF_BAR + 1024 + 256;
}

__global__ void __cluster_dims__(2, 1, 1) __launch_bounds__(384, 1)
k3_out(const __grid_constant__ CUtensorMap tmo, const __grid_constant__ CUtensorMap tmw,
       const __grid_constant__ CUtensorMap tmbt, const __grid_constant__ CUtensorMap tmout) {
  using namespace k3;
  extern __shared__ uint8_t smem_raw[];
  const uint32_t sbase = (smem_u32(smem_raw) + 1023) & ~1023u;
  uint8_t* sgen = smem_raw + (sbase - smem_u32(smem_raw));
  const uint32_t bars = sbase + OFF_BAR;
  const uint32_t barbt = bars + 8 * 2 * ST;
  const int tid = threadIdx.x, warp = tid >> 5, lane = tid & 31;
  const uint32_t rank = cluster_ctarank();
  const int cl = blockIdx.x >> 1;
  const int mt = cl >> 2;
  const int nt = ((cl & 3) << 1) + rank;
  const int m0 = mt * BM, n0 = nt * BN;

  if (tid == 0) {
    for (int s = 0; s < ST; s++) {
      mbar_init(bars + 8 * s, 1);
      mbar_init(bars + 8 * (ST + s), 16);
    }
    mbar_init(barbt, 1);
    asm volatile("fence.mbarrier_init.release.cluster;" ::: "memory");
  }
  cluster_sync_all();

  if (warp >= 8) {
    asm volatile("setmaxnreg.dec.sync.aligned.u32 40;");
    if (warp == 8 && lane == 0) {
      for (int kb = 0; kb < ST; kb++) {
        const uint32_t full = bars + 8 * kb;
        mbar_expect_tx(full, STAGE);
        const uint32_t sb = sbase + kb * STAGE + A_BYTES;
#pragma unroll
        for (int j = 0; j < 2; j++) tma_load_2d(sb + j * 8192, &tmw, full, n0 + j * 64, kb * BK);
      }
      pdl_wait();
      if (blockIdx.x == 0) for (int i = 0; i < 16; i++) g_cnt[i] = 0;
      for (int kb = 0; kb < DM / BK; kb++) {
        const int s = kb % ST;
        const uint32_t full = bars + 8 * s;
        const uint32_t sa = sbase + s * STAGE, sb = sa + A_BYTES;
        if (kb >= ST) {
          mbar_wait(bars + 8 * (ST + s), ((kb / ST) & 1) ^ 1);
          mbar_expect_tx(full, STAGE);
#pragma unroll
          for (int j = 0; j < 2; j++) tma_load_2d(sb + j * 8192, &tmw, full, n0 + j * 64, kb * BK);
        }
        tma_load_2d_mc(sa + rank * 8192, &tmo, full, kb * BK, m0 + rank * 64, (uint16_t)3);
        if (kb == 2) {
          mbar_expect_tx(barbt, 32768);
          tma_load_2d(sbase + OFF_BT, &tmbt, barbt, m0, n0);
          tma_load_2d(sbase + OFF_BT + 16384, &tmbt, barbt, m0 + 64, n0);
        }
      }
    }
    cluster_sync_all();
  } else {
    asm volatile("setmaxnreg.inc.sync.aligned.u32 232;");
    const int wg = warp >> 2, w4 = warp & 3, g = lane >> 2, t = lane & 3;
    if (tid == 0) TS(3, 0);
    float acc[64];
#pragma unroll
    for (int i = 0; i < 64; i++) acc[i] = 0.f;
    for (int kb = 0; kb < DM / BK; kb++) {
      const int s = kb % ST;
      mbar_wait(bars + 8 * s, (kb / ST) & 1);
      const uint32_t sa = sbase + s * STAGE + wg * 8192, sb = sbase + s * STAGE + A_BYTES;
      wg_fence();
#pragma unroll
      for (int ks = 0; ks < 4; ks++) {
        const uint64_t db = make_desc(sb + ks * 2048, 8192, 1024);
        const uint64_t da = make_desc(sa + ks * 32, 16, 1024);
        wgmma_ss_n128_tb(acc, da, db, 1);
      }
      wg_commit();
      if (kb > 0) {
        wg_wait<1>();
        const int sp = (kb - 1) % ST;
        if (lane == 0) { mbar_arrive_cluster(bars + 8 * (ST + sp), 0); mbar_arrive_cluster(bars + 8 * (ST + sp), 1); }
      }
    }
    wg_wait<0>();
    fence_regs(acc);
    if (tid == 0) TS(3, 1);
    named_bar_sync(1, 256);
    mbar_wait(barbt, 0);
    pdl_wait();
#pragma unroll
    for (int h = 0; h < 2; h++) {
      const int rl = wg * 64 + w4 * 16 + g + h * 8;
      const float gt = g_gate[m0 + rl];
      const float omg = bfr(1.0f - gt);
      const uint8_t* bt = sgen + OFF_BT + wg * 16384;
      const int ll = rl & 63;
#pragma unroll
      for (int j = 0; j < 16; j++) {
        const int c = 8 * j + 2 * t;
        const float b0 = __bfloat162float(*reinterpret_cast<const bf16*>(bt + c * 128 + (((ll >> 3) ^ (c & 7)) << 4) + (ll & 7) * 2));
        const float b1 = __bfloat162float(*reinterpret_cast<const bf16*>(bt + (c + 1) * 128 + (((ll >> 3) ^ ((c + 1) & 7)) << 4) + (ll & 7) * 2));
        const uint32_t a2 = pack2(acc[4 * j + 2 * h], acc[4 * j + 2 * h + 1]);
        const float o0 = bfr(gt * lo_f(a2)) + bfr(omg * b0);
        const float o1 = bfr(gt * hi_f(a2)) + bfr(omg * b1);
        *reinterpret_cast<uint32_t*>(sgen + (j >> 3) * 16384 + rl * 128 + (((j & 7) ^ (rl & 7)) << 4) + t * 4) = pack2(o0, o1);
      }
    }
    fence_async_smem();
    if (tid == 0) TS(3, 2);
    named_bar_sync(2 + wg, 128);
    if ((tid & 127) == 0) {
#pragma unroll
      for (int j = 0; j < 2; j++)
        asm volatile("cp.async.bulk.tensor.2d.global.shared::cta.bulk_group [%0, {%2, %3}], [%1];" ::"l"(&tmout),
                     "r"(sbase + j * 16384 + wg * 8192), "r"(n0 + j * 64), "r"(m0 + wg * 64) : "memory");
      asm volatile("cp.async.bulk.commit_group;" ::: "memory");
      asm volatile("cp.async.bulk.wait_group.read 0;" ::: "memory");
      if (tid == 0) TS(3, 3);
    }
    cluster_sync_all();
  }
}

__device__ __align__(1024) bf16 g_bT[DM * SEQ];
constexpr int KOFF = 2048 + 16;
constexpr int KSZ = 2112;
constexpr int KCH = 2 * KSZ + 16;

__device__ __forceinline__ void mma_bf16(float (&d)[4], uint32_t a0, uint32_t a1, uint32_t a2, uint32_t a3, uint32_t b0, uint32_t b1) {
  asm volatile("mma.sync.aligned.m16n8k16.row.col.f32.bf16.bf16.f32 {%0,%1,%2,%3}, {%4,%5,%6,%7}, {%8,%9}, {%0,%1,%2,%3};"
               : "+f"(d[0]), "+f"(d[1]), "+f"(d[2]), "+f"(d[3]) : "r"(a0), "r"(a1), "r"(a2), "r"(a3), "r"(b0), "r"(b1));
}
__device__ __forceinline__ void mma_f16(float (&d)[4], uint32_t a0, uint32_t a1, uint32_t a2, uint32_t a3, uint32_t b0, uint32_t b1) {
  asm volatile("mma.sync.aligned.m16n8k16.row.col.f32.f16.f16.f32 {%0,%1,%2,%3}, {%4,%5,%6,%7}, {%8,%9}, {%0,%1,%2,%3};"
               : "+f"(d[0]), "+f"(d[1]), "+f"(d[2]), "+f"(d[3]) : "r"(a0), "r"(a1), "r"(a2), "r"(a3), "r"(b0), "r"(b1));
}
struct cf { float r, i; };
__device__ __forceinline__ cf cmul(cf a, cf b) { cf c; c.r = a.r * b.r - a.i * b.i; c.i = a.r * b.i + a.i * b.r; return c; }
__device__ __forceinline__ cf csq(cf a) { cf c; c.r = a.r * a.r - a.i * a.i; c.i = 2.f * a.r * a.i; return c; }
__device__ __forceinline__ cf cexpp(float ar, float ai, float p) {
  const float e = ex2f(ar * p * 1.4426950408889634f);
  const float th = ai * p;
  const float k = rintf(th * 0.15915494309189535f);
  float r = fmaf(k, -6.2831854820251465f, th);
  r = fmaf(k, 1.7484556000744e-7f, r);
  cf w; w.r = e * __cosf(r); w.i = e * __sinf(r); return w;
}
__device__ __forceinline__ uint32_t packh(float lo, float hi) {
  uint32_t r; asm("cvt.rn.f16x2.f32 %0, %1, %2;" : "=r"(r) : "f"(hi), "f"(lo)); return r;
}

namespace k2 {
constexpr int CH = 8;
constexpr int UPAD = 128;
constexpr int USZ = UPAD + SEQ;
constexpr int TSTR = 40;
constexpr int TABW = 72 * TSTR;
constexpr int PAIRW = 2 * TABW;
constexpr int P_K = 0;
constexpr int P_Q = KCH / 2;
constexpr int P_B = P_Q + 2 * 648;
constexpr int P_R = P_B + 324 + 4;
constexpr int OFF_U = 0;
constexpr int OFF_P = OFF_U + CH * USZ * 2;
constexpr int PW2 = P_R + 2048;
constexpr int SMEM = OFF_P + CH * PW2 * 4;
static_assert(PW2 >= PAIRW && (P_R % 4) == 0 && (PW2 % 4) == 0, "layout");
}

__global__ void __launch_bounds__(512, 1)
k2_ssm(const bf16* __restrict__ x, const bf16* __restrict__ logAr, const bf16* __restrict__ Aim, const bf16* __restrict__ Cre,
       const bf16* __restrict__ Cim, const bf16* __restrict__ logdt, const bf16* __restrict__ Dskip) {
  using namespace k2;
  extern __shared__ __align__(16) uint8_t sm[];
  const int tid = threadIdx.x, warp = tid >> 5, lane = tid & 31, g = lane >> 2, t = lane & 3;
  const int ch = warp >> 1, half = warp & 1, l64 = half * 32 + lane;
  const int d0 = blockIdx.x * CH;
  bf16* us = reinterpret_cast<bf16*>(sm + OFF_U);
  uint32_t* pw = reinterpret_cast<uint32_t*>(sm + OFF_P) + ch * PW2;
  if (tid == 0) TS(2, 0);
  pdl_launch();

  uint4 uv[2][2];
#pragma unroll
  for (int it = 0; it < 2; it++) {
    const int l = 2 * (tid + it * 512);
    uv[it][0] = __ldg(reinterpret_cast<const uint4*>(x + (size_t)l * DM + d0));
    uv[it][1] = __ldg(reinterpret_cast<const uint4*>(x + (size_t)(l + 1) * DM + d0));
  }
  const int d = d0 + ch;
  bf16 p_la[2], p_ai[2], p_cr[2], p_ci[2];
#pragma unroll
  for (int c = 0; c < 2; c++) {
    const int idx = d * NMODE + half * 64 + c * 32 + lane;
    p_la[c] = logAr[idx]; p_ai[c] = Aim[idx]; p_cr[c] = Cre[idx]; p_ci[c] = Cim[idx];
  }
  const bf16 p_dt = logdt[d];

  float acc[5][4];
#pragma unroll
  for (int a = 0; a < 5; a++)
#pragma unroll
    for (int b = 0; b < 4; b++) acc[a][b] = 0.f;
  float last = 0.f, scale;
  {
    const float dt = bfr(ex2f(__bfloat162float(p_dt) * 1.4426950408889634f));
    float cr[2], ci[2], arr[2], aii[2];
#pragma unroll
    for (int c = 0; c < 2; c++) {
      arr[c] = -bfr(ex2f(__bfloat162float(p_la[c]) * 1.4426950408889634f)) * dt;
      aii[c] = __bfloat162float(p_ai[c]) * dt;
      cr[c] = __bfloat162float(p_cr[c]) * dt;
      ci[c] = __bfloat162float(p_ci[c]) * dt;
    }
    float mx = fmaxf(fmaxf(fabsf(cr[0]), fabsf(ci[0])), fmaxf(fabsf(cr[1]), fabsf(ci[1])));
#pragma unroll
    for (int o = 16; o; o >>= 1) mx = fmaxf(mx, __shfl_xor_sync(0xffffffffu, mx, o));
    {
      int e = (int)((__float_as_uint(mx) >> 23) & 255u) + 1;
      e = e < 32 ? 32 : (e > 220 ? 220 : e);
      scale = __uint_as_float((uint32_t)e << 23);
    }
    const float iscale = __uint_as_float((uint32_t)(254 - ((__float_as_uint(scale) >> 23) & 255u)) << 23);
    uint32_t* tab = pw + half * TABW;
#pragma unroll 1
    for (int c = 0; c < 2; c++) {
      const float ar = arr[c], ai = aii[c];
      cf C; C.r = cr[c] * iscale; C.i = ci[c] * iscale;
      const cf W1 = cexpp(ar, ai, 1.f), W16 = cexpp(ar, ai, 16.f), W256 = cexpp(ar, ai, 256.f);
      const cf W512 = csq(W256), W1024 = csq(W512);
      const cf W1536 = cmul(W1024, W512);
      {
        const cf w2048 = csq(W1024);
        last += cr[c] * w2048.r - ci[c] * w2048.i;
      }
      uint32_t* tp = tab + lane;
      {
        cf xa = C;
#pragma unroll
        for (int i = 0; i < 16; i++) {
          const uint32_t pk = packh(xa.r, -xa.i);
          tp[i * TSTR] = pk;
          if ((i & 1) == 0) {
            tp[(16 + i / 2) * TSTR] = pk;
            const cf xb = cmul(xa, W256);
            tp[(24 + i / 2) * TSTR] = packh(xb.r, -xb.i);
          }
          xa = cmul(xa, W16);
        }
      }
      {
        cf y; y.r = 1.f; y.i = 0.f;
        const cf W528 = cmul(W512, W16);
        const cf WA16 = cmul(W1024, W16), WB16 = cmul(W1536, W16);
#pragma unroll
        for (int j = 0; j < 16; j++) {
          tp[(32 + j) * TSTR] = packh(y.r, y.i);
          if ((j & 1) == 0) { const cf z = cmul(y, W256); tp[(48 + j / 2) * TSTR] = packh(z.r, z.i); }
          if ((j & 3) == 0) {
            const cf z0 = cmul(y, W512), z1 = cmul(y, W528);
            tp[(56 + j / 4) * TSTR] = packh(z0.r, z0.i);
            tp[(60 + j / 4) * TSTR] = packh(z1.r, z1.i);
          }
          if ((j & 7) == 0) {
            const cf z0 = cmul(y, W1024), z1 = cmul(y, WA16), z2 = cmul(y, W1536), z3 = cmul(y, WB16);
            tp[(64 + j / 8) * TSTR] = packh(z0.r, z0.i);
            tp[(66 + j / 8) * TSTR] = packh(z1.r, z1.i);
            tp[(68 + j / 8) * TSTR] = packh(z2.r, z2.i);
            tp[(70 + j / 8) * TSTR] = packh(z3.r, z3.i);
          }
          y = cmul(y, W1);
        }
      }
      __syncwarp();
#pragma unroll
      for (int ks4 = 0; ks4 < 4; ks4++) {
        const uint32_t* fp = tab + 8 * ks4 + 2 * t;
        const uint2 xa0 = *reinterpret_cast<const uint2*>(fp + g * TSTR), xa1 = *reinterpret_cast<const uint2*>(fp + (g + 8) * TSTR);
        const uint2 xb0 = *reinterpret_cast<const uint2*>(fp + (16 + g) * TSTR), xb1 = *reinterpret_cast<const uint2*>(fp + (24 + g) * TSTR);
        const uint2 y1 = *reinterpret_cast<const uint2*>(fp + (32 + g) * TSTR), y2 = *reinterpret_cast<const uint2*>(fp + (40 + g) * TSTR);
        const uint2 y3 = *reinterpret_cast<const uint2*>(fp + (48 + g) * TSTR), y4 = *reinterpret_cast<const uint2*>(fp + (56 + g) * TSTR);
        const uint2 y5 = *reinterpret_cast<const uint2*>(fp + (64 + g) * TSTR);
        mma_f16(acc[0], xa0.x, xa1.x, xa0.y, xa1.y, y1.x, y1.y);
        mma_f16(acc[1], xa0.x, xa1.x, xa0.y, xa1.y, y2.x, y2.y);
        mma_f16(acc[2], xa0.x, xa1.x, xa0.y, xa1.y, y3.x, y3.y);
        mma_f16(acc[3], xb0.x, xb1.x, xb0.y, xb1.y, y4.x, y4.y);
        mma_f16(acc[4], xb0.x, xb1.x, xb0.y, xb1.y, y5.x, y5.y);
      }
      __syncwarp();
    }
  }
  if (tid == 0) TS(2, 1);
  if (tid < CH * UPAD / 2) {
    const int c = tid / (UPAD / 2), o = tid % (UPAD / 2);
    reinterpret_cast<uint32_t*>(us + c * USZ)[o] = 0u;
  }
#pragma unroll
  for (int it = 0; it < 2; it++) {
    const int l = 2 * (tid + it * 512);
    const int e = l & 15;
    const int pe = ((e & 7) >> 1) * 4 + (e >> 3) * 2;
    const int pos = UPAD + (l & ~15) + pe;
    const uint32_t a[4] = {uv[it][0].x, uv[it][0].y, uv[it][0].z, uv[it][0].w};
    const uint32_t b[4] = {uv[it][1].x, uv[it][1].y, uv[it][1].z, uv[it][1].w};
#pragma unroll
    for (int c = 0; c < 4; c++) {
      *reinterpret_cast<uint32_t*>(us + (2 * c) * USZ + pos) = __byte_perm(a[c], b[c], 0x5410);
      *reinterpret_cast<uint32_t*>(us + (2 * c + 1) * USZ + pos) = __byte_perm(a[c], b[c], 0x7632);
    }
  }
  named_bar_sync(1 + ch, 64);
  float* kqp = reinterpret_cast<float*>(pw + P_Q);
  {
    float* kq = kqp + half * 648;
    const float sc2 = 2.f * scale;
#pragma unroll
    for (int h = 0; h < 2; h++) {
      const int i = g + 8 * h;
      *reinterpret_cast<float2*>(kq + 16 * i + 2 * t) = make_float2(sc2 * acc[0][2 * h], sc2 * acc[0][2 * h + 1]);
      *reinterpret_cast<float2*>(kq + 16 * i + 8 + 2 * t) = make_float2(sc2 * acc[1][2 * h], sc2 * acc[1][2 * h + 1]);
      *reinterpret_cast<float2*>(kq + 256 + 8 * i + 2 * t) = make_float2(sc2 * acc[2][2 * h], sc2 * acc[2][2 * h + 1]);
      *reinterpret_cast<float2*>(kq + 384 + 8 * i + 2 * t) = make_float2(sc2 * acc[3][2 * h], sc2 * acc[3][2 * h + 1]);
      *reinterpret_cast<float2*>(kq + 512 + 4 * i + 64 * (t >> 1) + 2 * (t & 1)) = make_float2(sc2 * acc[4][2 * h], sc2 * acc[4][2 * h + 1]);
    }
#pragma unroll
    for (int o = 16; o; o >>= 1) last += __shfl_xor_sync(0xffffffffu, last, o);
    if (lane == 0) kq[640] = 2.f * last;
  }
  named_bar_sync(1 + ch, 64);
  bf16* kb = reinterpret_cast<bf16*>(pw + P_B);
  for (int i = l64; i < 324; i += 64) {
    const float2 a = *reinterpret_cast<const float2*>(kqp + 2 * i), b = *reinterpret_cast<const float2*>(kqp + 648 + 2 * i);
    pw[P_B + i] = pack2(a.x + b.x, a.y + b.y);
  }
  named_bar_sync(1 + ch, 64);
  {
    for (int v = l64; v < KSZ / 8; v += 64) {
      uint32_t kv[9];
#pragma unroll
      for (int q = 0; q < 9; q++) {
        const int xk = KOFF - 8 * v - q;
        uint32_t val = 0u;
        if (xk >= 0 && xk < SEQ) {
          const int ls = xk < 256 ? 0 : (xk < 512 ? 1 : (xk < 1024 ? 2 : 3));
          const int qn = ls == 0 ? xk : ((xk + ((1 << ls) >> 1) - 1 + ((xk >> ls) & 1)) >> ls);
          val = reinterpret_cast<const uint16_t*>(kb)[128 * ls + qn];
        }
        kv[q] = val;
      }
      *reinterpret_cast<uint4*>(pw + P_K + 4 * v) =
          make_uint4(kv[0] | (kv[1] << 16), kv[2] | (kv[3] << 16), kv[4] | (kv[5] << 16), kv[6] | (kv[7] << 16));
      *reinterpret_cast<uint4*>(pw + P_K + (KSZ + 16) / 2 + 4 * v) =
          make_uint4(kv[1] | (kv[2] << 16), kv[3] | (kv[4] << 16), kv[5] | (kv[6] << 16), kv[7] | (kv[8] << 16));
    }
  }
  __syncthreads();
  if (tid == 0) TS(2, 2);

  float D[16][4];
#pragma unroll
  for (int j = 0; j < 16; j++)
#pragma unroll
    for (int q = 0; q < 4; q++) D[j][q] = 0.f;
  const bf16* uc = us + ch * USZ + UPAD;
  {
    const uint32_t* fbase = pw + P_K + ((g & 1) ? (KSZ + 16) / 2 : 0) + ((KOFF - g + 2 * t) >> 1);
    for (int r = half * 4; r < half * 4 + 4; r++) {
      uint32_t B[16][2];
#pragma unroll
      for (int j = 0; j < 16; j++) {
        const uint2 v = *reinterpret_cast<const uint2*>(uc + 16 * (8 * j - r + g) + 4 * t);
        B[j][0] = v.x; B[j][1] = v.y;
      }
      uint32_t fm1 = fbase[-4 * (2 * r - 1)];
#pragma unroll
      for (int k = 0; k < 16; k++) {
        const int dl = 8 * k + r;
        const uint32_t f0 = fbase[-4 * (2 * dl)];
        const uint32_t f1 = fbase[-4 * (2 * dl + 1)];
        if (k > 0) fm1 = fbase[-4 * (2 * dl - 1)];
#pragma unroll
        for (int j = k; j < 16; j++) mma_bf16(D[j], f0, f1, fm1, f0, B[j - k][0], B[j - k][1]);
      }
    }
  }
  if (tid == 0) TS(2, 3);
  float* red = reinterpret_cast<float*>(pw + P_R);
#pragma unroll
  for (int j = 0; j < 8; j++) {
    const int jo = half ? j : j + 8;
    *reinterpret_cast<float4*>(red + (jo * 32 + lane) * 4) =
        make_float4(half ? D[j][0] : D[j + 8][0], half ? D[j][1] : D[j + 8][1], half ? D[j][2] : D[j + 8][2], half ? D[j][3] : D[j + 8][3]);
  }
  named_bar_sync(1 + ch, 64);
  {
    const float dsk = __bfloat162float(Dskip[d]);
    uint16_t* ys = reinterpret_cast<uint16_t*>(pw + P_K);
#pragma unroll
    for (int j = 0; j < 8; j++) {
      const int jm = half ? j + 8 : j;
      const float4 o = *reinterpret_cast<const float4*>(red + (jm * 32 + lane) * 4);
      const float dd[4] = {(half ? D[j + 8][0] : D[j][0]) + o.x, (half ? D[j + 8][1] : D[j][1]) + o.y,
                           (half ? D[j + 8][2] : D[j][2]) + o.z, (half ? D[j + 8][3] : D[j][3]) + o.w};
#pragma unroll
      for (int q = 0; q < 4; q++) {
        const int a = 8 * jm + 2 * t + (q & 1), bb = g + (q >> 1) * 8;
        const int pe = ((bb & 7) >> 1) * 4 + (bb >> 3) * 2 + (bb & 1);
        const float uvv = __bfloat162float(uc[16 * a + pe]);
        const float y = bfr(dd[q]) + bfr(uvv * dsk);
        ys[16 * a + bb] = (uint16_t)(__float_as_uint(bfr(y)) >> 16);
      }
    }
    __syncwarp();
    bf16* dst = g_bT + (size_t)d * SEQ + half * 1024;
#pragma unroll
    for (int i = 0; i < 4; i++) {
      const uint4 v = *reinterpret_cast<const uint4*>(ys + half * 1024 + (i * 32 + lane) * 8);
      *reinterpret_cast<uint4*>(dst + (i * 32 + lane) * 8) = v;
    }
  }
  if (tid == 0) TS(2, 4);
}

typedef CUresult (*EncodeFn)(CUtensorMap*, CUtensorMapDataType, cuuint32_t, void*, const cuuint64_t*, const cuuint64_t*,
                             const cuuint32_t*, const cuuint32_t*, CUtensorMapInterleave, CUtensorMapSwizzle,
                             CUtensorMapL2promotion, CUtensorMapFloatOOBfill);

static void make_map(EncodeFn enc, CUtensorMap* m, void* ptr, uint64_t inner, uint64_t outer, uint32_t bi, uint32_t bo) {
  cuuint64_t dims[2] = {inner, outer};
  cuuint64_t strides[1] = {inner * 2};
  cuuint32_t box[2] = {bi, bo};
  cuuint32_t es[2] = {1, 1};
  enc(m, CU_TENSOR_MAP_DATA_TYPE_BFLOAT16, 2, ptr, dims, strides, box, es, CU_TENSOR_MAP_INTERLEAVE_NONE,
      CU_TENSOR_MAP_SWIZZLE_128B, CU_TENSOR_MAP_L2_PROMOTION_L2_256B, CU_TENSOR_MAP_FLOAT_OOB_FILL_NONE);
}

extern "C" void kernel_launch(void* const* d_in, const int* in_sizes, int n_in, void* d_out, int out_size) {
  const bf16* x = (const bf16*)d_in[0];
  const bf16* wqkv = (const bf16*)d_in[1];
  const bf16* wo = (const bf16*)d_in[2];
  const bf16* logAr = (const bf16*)d_in[4];
  const bf16* Aim = (const bf16*)d_in[5];
  const bf16* Cre = (const bf16*)d_in[6];
  const bf16* Cim = (const bf16*)d_in[7];
  const bf16* logdt = (const bf16*)d_in[8];
  const bf16* Dskip = (const bf16*)d_in[9];
  const bf16* gatew = (const bf16*)d_in[10];

  static EncodeFn enc = nullptr;
  static void* p_o = nullptr;
  static void* p_bT = nullptr;
  if (!enc) {
    void* fn = nullptr;
    cudaDriverEntryPointQueryResult qr;
    cudaGetDriverEntryPoint("cuTensorMapEncodeTiled", &fn, cudaEnableDefault, &qr);
    enc = (EncodeFn)fn;
    cudaGetSymbolAddress(&p_o, g_o);
    cudaGetSymbolAddress(&p_bT, g_bT);
    cudaFuncSetAttribute(k1_qkv_attn, cudaFuncAttributeMaxDynamicSharedMemorySize, k1::SMEM);
    cudaFuncSetAttribute(k2_ssm, cudaFuncAttributeMaxDynamicSharedMemorySize, k2::SMEM);
    cudaFuncSetAttribute(k3_out, cudaFuncAttributeMaxDynamicSharedMemorySize, k3::SMEM);
  }
  CUtensorMap tmx, tmw, tmo, tmwo, tmbt, tmout;
  make_map(enc, &tmx, (void*)x, 1024, 2048, 64, 128);
  make_map(enc, &tmw, (void*)wqkv, 3072, 1024, 64, 64);
  make_map(enc, &tmo, p_o, 1024, 2048, 64, 64);
  make_map(enc, &tmwo, (void*)wo, 1024, 1024, 64, 64);
  make_map(enc, &tmbt, p_bT, 2048, 1024, 64, 128);
  make_map(enc, &tmout, d_out, 1024, 2048, 64, 64);

  k2_ssm<<<128, 512, k2::SMEM>>>(x, logAr, Aim, Cre, Cim, logdt, Dskip);
  cudaLaunchAttribute at[1];
  at[0].id = cudaLaunchAttributeProgrammaticStreamSerialization;
  at[0].val.programmaticStreamSerializationAllowed = 1;
  cudaLaunchConfig_t cfg = {};
  cfg.gridDim = dim3(128); cfg.blockDim = dim3(384); cfg.stream = cudaStreamPerThread; cfg.attrs = at; cfg.numAttrs = 1;
  cfg.dynamicSmemBytes = k1::SMEM;
  cudaLaunchKernelEx(&cfg, k1_qkv_attn, tmx, tmw, x, gatew);
  cfg.dynamicSmemBytes = k3::SMEM;
  cudaLaunchKernelEx(&cfg, k3_out, tmo, tmwo, tmbt, tmout);
}
```

```cpp
#include <cuda_runtime.h>
#include <cuda_bf16.h>
#include <cuda.h>
#include <stdint.h>

typedef __nv_bfloat16 bf16;

constexpr int SEQ = 2048, DM = 1024, NMODE = 128;

__device__ __align__(1024) bf16 g_o[SEQ * DM];
__device__ __align__(1024) bf16 g_b[SEQ * DM];
__device__ float g_gate[SEQ];
__device__ __align__(16) float g_part[16 * 8 * 2 * 1056];
__device__ unsigned int g_cnt[16];

#define TS(k, i) do {} while (0)
__device__ __forceinline__ uint32_t smem_u32(const void* p) { return (uint32_t)__cvta_generic_to_shared(p); }
__device__ __forceinline__ void mbar_init(uint32_t bar, uint32_t cnt) {
  asm volatile("mbarrier.init.shared::cta.b64 [%0], %1;" ::"r"(bar), "r"(cnt));
}
__device__ __forceinline__ void mbar_expect_tx(uint32_t bar, uint32_t bytes) {
  asm volatile("mbarrier.arrive.expect_tx.shared::cta.b64 _, [%0], %1;" ::"r"(bar), "r"(bytes) : "memory");
}
__device__ __forceinline__ void mbar_arrive_cluster(uint32_t bar, uint32_t cta) {
  asm volatile(
      "{\n.reg .b32 ra;\nmapa.shared::cluster.u32 ra, %0, %1;\n"
      "mbarrier.arrive.shared::cluster.b64 _, [ra];\n}\n" ::"r"(bar), "r"(cta) : "memory");
}
__device__ __forceinline__ bool mbar_try_wait(uint32_t bar, uint32_t parity) {
  uint32_t ok;
  asm volatile(
      "{\n.reg .pred p;\nmbarrier.try_wait.parity.shared::cta.b64 p, [%1], %2;\nselp.u32 %0, 1, 0, p;\n}\n"
      : "=r"(ok) : "r"(bar), "r"(parity) : "memory");
  return ok;
}
__device__ __forceinline__ void mbar_wait(uint32_t bar, uint32_t parity) {
  while (!mbar_try_wait(bar, parity)) {}
}
__device__ __forceinline__ void tma_load_2d(uint32_t dst, const CUtensorMap* map, uint32_t bar, int c0, int c1) {
  asm volatile(
      "cp.async.bulk.tensor.2d.shared::cluster.global.mbarrier::complete_tx::bytes [%0], [%1, {%3, %4}], [%2];" ::"r"(dst),
      "l"(map), "r"(bar), "r"(c0), "r"(c1) : "memory");
}
__device__ __forceinline__ void tma_load_2d_mc(uint32_t dst, const CUtensorMap* map, uint32_t bar, int c0, int c1,
                                               uint16_t mask) {
  asm volatile(
      "cp.async.bulk.tensor.2d.shared::cluster.global.mbarrier::complete_tx::bytes.multicast::cluster [%0], [%1, {%3, %4}], [%2], %5;" ::"r"(dst),
      "l"(map), "r"(bar), "r"(c0), "r"(c1), "h"(mask) : "memory");
}
__device__ __forceinline__ void cluster_sync_all() {
  asm volatile("barrier.cluster.arrive.release.aligned;\nbarrier.cluster.wait.acquire.aligned;\n" ::: "memory");
}
__device__ __forceinline__ uint32_t cluster_ctarank() {
  uint32_t r; asm volatile("mov.u32 %0, %%cluster_ctarank;" : "=r"(r)); return r;
}
__device__ __forceinline__ void pdl_wait() { asm volatile("griddepcontrol.wait;" ::: "memory"); }
__device__ __forceinline__ void pdl_launch() { asm volatile("griddepcontrol.launch_dependents;" ::: "memory"); }
__device__ __forceinline__ void named_bar_sync(int id, int n) { asm volatile("bar.sync %0, %1;" ::"r"(id), "r"(n) : "memory"); }
__device__ __forceinline__ void fence_async_smem() { asm volatile("fence.proxy.async.shared::cta;" ::: "memory"); }
__device__ __forceinline__ void wg_fence() { asm volatile("wgmma.fence.sync.aligned;" ::: "memory"); }
__device__ __forceinline__ void wg_commit() { asm volatile("wgmma.commit_group.sync.aligned;" ::: "memory"); }
template <int N> __device__ __forceinline__ void wg_wait() { asm volatile("wgmma.wait_group.sync.aligned %0;" ::"n"(N) : "memory"); }
__device__ __forceinline__ uint64_t make_desc(uint32_t addr, uint32_t lbo, uint32_t sbo) {
  return (uint64_t)((addr & 0x3FFFF) >> 4) | ((uint64_t)(lbo >> 4) << 16) | ((uint64_t)(sbo >> 4) << 32) | (1ull << 62);
}
__device__ __forceinline__ float bfr(float x) { return __bfloat162float(__float2bfloat16_rn(x)); }
__device__ __forceinline__ uint32_t pack2(float lo, float hi) {
  __nv_bfloat162 v = __floats2bfloat162_rn(lo, hi);
  return *reinterpret_cast<uint32_t*>(&v);
}
__device__ __forceinline__ float ex2f(float x) { float r; asm("ex2.approx.ftz.f32 %0, %1;" : "=f"(r) : "f"(x)); return r; }
__device__ __forceinline__ float lo_f(uint32_t v) { return __uint_as_float(v << 16); }
__device__ __forceinline__ float hi_f(uint32_t v) { return __uint_as_float(v & 0xffff0000u); }
__device__ __forceinline__ uint32_t phi2(float a0, float a1) {
  const uint32_t t2 = pack2(a0, a1);
  const float t0 = lo_f(t2), t1 = hi_f(t2);
  const float e0 = ex2f(t0 * 1.4426950408889634f), e1 = ex2f(t1 * 1.4426950408889634f);
  const float f0 = t0 > 0.f ? t0 + 1.0f : e0;
  const float f1 = t1 > 0.f ? t1 + 1.0f : e1;
  const uint32_t f2 = pack2(f0, f1);
  return pack2(lo_f(f2) + 1e-6f, hi_f(f2) + 1e-6f);
}
template <int R> __device__ __forceinline__ void fence_regs(float (&d)[R]) {
#pragma unroll
  for (int i = 0; i < R; i++) asm volatile("" : "+f"(d[i])::"memory");
}

__device__ __forceinline__ void wgmma_ss_n192_tb(float (&d)[96], uint64_t da, uint64_t db, int sc) {
  asm volatile("{\n.reg .pred p;\nsetp.ne.b32 p, %98, 0;\n"
    "wgmma.mma_async.sync.aligned.m64n192k16.f32.bf16.bf16 {%0, %1, %2, %3, %4, %5, %6, %7, %8, %9, %10, %11, %12, %13, %14, %15, %16, %17, %18, %19, %20, %21, %22, %23, %24, %25, %26, %27, %28, %29, %30, %31, %32, %33, %34, %35, %36, %37, %38, %39, %40, %41, %42, %43, %44, %45, %46, %47, %48, %49, %50, %51, %52, %53, %54, %55, %56, %57, %58, %59, %60, %61, %62, %63, %64, %65, %66, %67, %68, %69, %70, %71, %72, %73, %74, %75, %76, %77, %78, %79, %80, %81, %82, %83, %84, %85, %86, %87, %88, %89, %90, %91, %92, %93, %94, %95}, %96, %97, p, 1, 1, 0, 1;\n}\n"
    : "+f"(d[0]), "+f"(d[1]), "+f"(d[2]), "+f"(d[3]), "+f"(d[4]), "+f"(d[5]), "+f"(d[6]), "+f"(d[7]), "+f"(d[8]), "+f"(d[9]), "+f"(d[10]), "+f"(d[11]), "+f"(d[12]), "+f"(d[13]), "+f"(d[14]), "+f"(d[15]), "+f"(d[16]), "+f"(d[17]), "+f"(d[18]), "+f"(d[19]), "+f"(d[20]), "+f"(d[21]), "+f"(d[22]), "+f"(d[23]), "+f"(d[24]), "+f"(d[25]), "+f"(d[26]), "+f"(d[27]), "+f"(d[28]), "+f"(d[29]), "+f"(d[30]), "+f"(d[31]), "+f"(d[32]), "+f"(d[33]), "+f"(d[34]), "+f"(d[35]), "+f"(d[36]), "+f"(d[37]), "+f"(d[38]), "+f"(d[39]), "+f"(d[40]), "+f"(d[41]), "+f"(d[42]), "+f"(d[43]), "+f"(d[44]), "+f"(d[45]), "+f"(d[46]), "+f"(d[47]), "+f"(d[48]), "+f"(d[49]), "+f"(d[50]), "+f"(d[51]), "+f"(d[52]), "+f"(d[53]), "+f"(d[54]), "+f"(d[55]), "+f"(d[56]), "+f"(d[57]), "+f"(d[58]), "+f"(d[59]), "+f"(d[60]), "+f"(d[61]), "+f"(d[62]), "+f"(d[63]), "+f"(d[64]), "+f"(d[65]), "+f"(d[66]), "+f"(d[67]), "+f"(d[68]), "+f"(d[69]), "+f"(d[70]), "+f"(d[71]), "+f"(d[72]), "+f"(d[73]), "+f"(d[74]), "+f"(d[75]), "+f"(d[76]), "+f"(d[77]), "+f"(d[78]), "+f"(d[79]), "+f"(d[80]), "+f"(d[81]), "+f"(d[82]), "+f"(d[83]), "+f"(d[84]), "+f"(d[85]), "+f"(d[86]), "+f"(d[87]), "+f"(d[88]), "+f"(d[89]), "+f"(d[90]), "+f"(d[91]), "+f"(d[92]), "+f"(d[93]), "+f"(d[94]), "+f"(d[95])
    : "l"(da), "l"(db), "r"(sc));
}

__device__ __forceinline__ void wgmma_ss_n128_tb(float (&d)[64], uint64_t da, uint64_t db, int sc) {
  asm volatile("{\n.reg .pred p;\nsetp.ne.b32 p, %66, 0;\n"
    "wgmma.mma_async.sync.aligned.m64n128k16.f32.bf16.bf16 {%0, %1, %2, %3, %4, %5, %6, %7, %8, %9, %10, %11, %12, %13, %14, %15, %16, %17, %18, %19, %20, %21, %22, %23, %24, %25, %26, %27, %28, %29, %30, %31, %32, %33, %34, %35, %36, %37, %38, %39, %40, %41, %42, %43, %44, %45, %46, %47, %48, %49, %50, %51, %52, %53, %54, %55, %56, %57, %58, %59, %60, %61, %62, %63}, %64, %65, p, 1, 1, 0, 1;\n}\n"
    : "+f"(d[0]), "+f"(d[1]), "+f"(d[2]), "+f"(d[3]), "+f"(d[4]), "+f"(d[5]), "+f"(d[6]), "+f"(d[7]), "+f"(d[8]), "+f"(d[9]), "+f"(d[10]), "+f"(d[11]), "+f"(d[12]), "+f"(d[13]), "+f"(d[14]), "+f"(d[15]), "+f"(d[16]), "+f"(d[17]), "+f"(d[18]), "+f"(d[19]), "+f"(d[20]), "+f"(d[21]), "+f"(d[22]), "+f"(d[23]), "+f"(d[24]), "+f"(d[25]), "+f"(d[26]), "+f"(d[27]), "+f"(d[28]), "+f"(d[29]), "+f"(d[30]), "+f"(d[31]), "+f"(d[32]), "+f"(d[33]), "+f"(d[34]), "+f"(d[35]), "+f"(d[36]), "+f"(d[37]), "+f"(d[38]), "+f"(d[39]), "+f"(d[40]), "+f"(d[41]), "+f"(d[42]), "+f"(d[43]), "+f"(d[44]), "+f"(d[45]), "+f"(d[46]), "+f"(d[47]), "+f"(d[48]), "+f"(d[49]), "+f"(d[50]), "+f"(d[51]), "+f"(d[52]), "+f"(d[53]), "+f"(d[54]), "+f"(d[55]), "+f"(d[56]), "+f"(d[57]), "+f"(d[58]), "+f"(d[59]), "+f"(d[60]), "+f"(d[61]), "+f"(d[62]), "+f"(d[63])
    : "l"(da), "l"(db), "r"(sc));
}

__device__ __forceinline__ void wgmma_ss_n64_tatb(float (&d)[32], uint64_t da, uint64_t db, int sc) {
  asm volatile("{\n.reg .pred p;\nsetp.ne.b32 p, %34, 0;\n"
    "wgmma.mma_async.sync.aligned.m64n64k16.f32.bf16.bf16 {%0, %1, %2, %3, %4, %5, %6, %7, %8, %9, %10, %11, %12, %13, %14, %15, %16, %17, %18, %19, %20, %21, %22, %23, %24, %25, %26, %27, %28, %29, %30, %31}, %32, %33, p, 1, 1, 1, 1;\n}\n"
    : "+f"(d[0]), "+f"(d[1]), "+f"(d[2]), "+f"(d[3]), "+f"(d[4]), "+f"(d[5]), "+f"(d[6]), "+f"(d[7]), "+f"(d[8]), "+f"(d[9]), "+f"(d[10]), "+f"(d[11]), "+f"(d[12]), "+f"(d[13]), "+f"(d[14]), "+f"(d[15]), "+f"(d[16]), "+f"(d[17]), "+f"(d[18]), "+f"(d[19]), "+f"(d[20]), "+f"(d[21]), "+f"(d[22]), "+f"(d[23]), "+f"(d[24]), "+f"(d[25]), "+f"(d[26]), "+f"(d[27]), "+f"(d[28]), "+f"(d[29]), "+f"(d[30]), "+f"(d[31])
    : "l"(da), "l"(db), "r"(sc));
}

__device__ __forceinline__ void wgmma_ss_n8_tatb(float (&d)[4], uint64_t da, uint64_t db, int sc) {
  asm volatile("{\n.reg .pred p;\nsetp.ne.b32 p, %6, 0;\n"
    "wgmma.mma_async.sync.aligned.m64n8k16.f32.bf16.bf16 {%0, %1, %2, %3}, %4, %5, p, 1, 1, 1, 1;\n}\n"
    : "+f"(d[0]), "+f"(d[1]), "+f"(d[2]), "+f"(d[3])
    : "l"(da), "l"(db), "r"(sc));
}

__device__ __forceinline__ void wgmma_rs_n40_tb(float (&d)[20], uint32_t a0, uint32_t a1, uint32_t a2, uint32_t a3, uint64_t db, int sc) {
  asm volatile("{\n.reg .pred p;\nsetp.ne.b32 p, %25, 0;\n"
    "wgmma.mma_async.sync.aligned.m64n40k16.f32.bf16.bf16 {%0, %1, %2, %3, %4, %5, %6, %7, %8, %9, %10, %11, %12, %13, %14, %15, %16, %17, %18, %19}, {%20, %21, %22, %23}, %24, p, 1, 1, 1;\n}\n"
    : "+f"(d[0]), "+f"(d[1]), "+f"(d[2]), "+f"(d[3]), "+f"(d[4]), "+f"(d[5]), "+f"(d[6]), "+f"(d[7]), "+f"(d[8]), "+f"(d[9]), "+f"(d[10]), "+f"(d[11]), "+f"(d[12]), "+f"(d[13]), "+f"(d[14]), "+f"(d[15]), "+f"(d[16]), "+f"(d[17]), "+f"(d[18]), "+f"(d[19])
    : "r"(a0), "r"(a1), "r"(a2), "r"(a3), "l"(db), "r"(sc));
}

namespace k1 {
constexpr int BM = 256, BN = 192, BK = 64, ST = 4;
constexpr int A_BYTES = BM * BK * 2, B_BYTES = BK * BN * 2, STAGE = A_BYTES + B_BYTES;
constexpr int SMEM = ST * STAGE + 1024 + 256;
constexpr int OFF_PK = 0, OFF_V = 32768, OFF_ONES = 65536, OFF_KV = 69632, OFF_O = 81920, OFF_RED = 114688;
}

__global__ void __cluster_dims__(2, 1, 1) __launch_bounds__(384, 1)
k1_qkv_attn(const __grid_constant__ CUtensorMap tmx, const __grid_constant__ CUtensorMap tmw,
            const bf16* __restrict__ x, const bf16* __restrict__ gatew, const bf16* __restrict__ p0,
            const bf16* __restrict__ p1, const bf16* __restrict__ p2, const bf16* __restrict__ p3) {
  using namespace k1;
  extern __shared__ uint8_t smem_raw[];
  const uint32_t sbase = (smem_u32(smem_raw) + 1023) & ~1023u;
  uint8_t* sgen = smem_raw + (sbase - smem_u32(smem_raw));
  const uint32_t bars = sbase + ST * STAGE;
  const int tid = threadIdx.x, warp = tid >> 5, lane = tid & 31;
  const uint32_t rank = cluster_ctarank();
  const int cl = blockIdx.x >> 1;
  const int mt = cl >> 3;
  const int hp = ((cl & 7) << 1) + rank;
  const int m0 = mt * BM;

  if (tid == 0) {
    for (int s = 0; s < ST; s++) {
      mbar_init(bars + 8 * s, 1);
      mbar_init(bars + 8 * (ST + s), 16);
    }
    asm volatile("fence.mbarrier_init.release.cluster;" ::: "memory");
  }
  cluster_sync_all();
  pdl_launch();

  if (warp >= 8) {
    asm volatile("setmaxnreg.dec.sync.aligned.u32 40;");
    if (warp == 8 && lane == 0) {
      for (int kb = 0; kb < DM / BK; kb++) {
        const int s = kb % ST;
        mbar_wait(bars + 8 * (ST + s), ((kb / ST) & 1) ^ 1);
        const uint32_t full = bars + 8 * s;
        mbar_expect_tx(full, STAGE);
        const uint32_t sa = sbase + s * STAGE, sb = sa + A_BYTES;
        tma_load_2d_mc(sa + rank * 16384, &tmx, full, kb * BK, m0 + rank * 128, (uint16_t)3);
#pragma unroll
        for (int j = 0; j < 3; j++) tma_load_2d(sb + j * 8192, &tmw, full, j * 1024 + hp * 64, kb * BK);
      }
    } else if (warp > 8) {
      if (warp == 9 && lane < 16) {
        const size_t o = (size_t)blockIdx.x * 1024 + lane * 64;
        asm volatile("prefetch.global.L2 [%0];" ::"l"(p0 + o));
        asm volatile("prefetch.global.L2 [%0];" ::"l"(p1 + o));
        asm volatile("prefetch.global.L2 [%0];" ::"l"(p2 + o));
        asm volatile("prefetch.global.L2 [%0];" ::"l"(p3 + o));
      }
      for (int rr = warp - 9; rr < 16; rr += 3) {
        const int r = blockIdx.x * 16 + rr;
        float s = 0.f;
#pragma unroll
        for (int c = lane * 8; c < DM; c += 256) {
          const uint4 xv = __ldg(reinterpret_cast<const uint4*>(x + (size_t)r * DM + c));
          const uint4 wv = __ldg(reinterpret_cast<const uint4*>(gatew + c));
          const bf16* xp = reinterpret_cast<const bf16*>(&xv);
          const bf16* wp = reinterpret_cast<const bf16*>(&wv);
#pragma unroll
          for (int q = 0; q < 8; q++) s += bfr(__bfloat162float(xp[q]) * __bfloat162float(wp[q]));
        }
#pragma unroll
        for (int o = 16; o; o >>= 1) s += __shfl_xor_sync(0xffffffffu, s, o);
        if (lane == 0) { const float z = bfr(s); g_gate[r] = bfr(1.0f / (1.0f + ex2f(-z * 1.4426950408889634f))); }
      }
    }
    __syncwarp();
    cluster_sync_all();
  } else {
    asm volatile("setmaxnreg.inc.sync.aligned.u32 232;");
    const int wg = warp >> 2, w4 = warp & 3, g = lane >> 2, t = lane & 3;
    if (tid == 0) TS(1, 0);
    float acc[2][96];
#pragma unroll
    for (int i = 0; i < 96; i++) { acc[0][i] = 0.f; acc[1][i] = 0.f; }
    for (int kb = 0; kb < DM / BK; kb++) {
      const int s = kb % ST;
      mbar_wait(bars + 8 * s, (kb / ST) & 1);
      const uint32_t sa = sbase + s * STAGE + wg * 16384, sb = sbase + s * STAGE + A_BYTES;
      wg_fence();
#pragma unroll
      for (int ks = 0; ks < 4; ks++) {
        const uint64_t db = make_desc(sb + ks * 2048, 8192, 1024);
#pragma unroll
        for (int mb = 0; mb < 2; mb++) {
          const uint64_t da = make_desc(sa + mb * 8192 + ks * 32, 16, 1024);
          wgmma_ss_n192_tb(acc[mb], da, db, 1);
        }
      }
      wg_commit();
      if (kb > 0) {
        wg_wait<1>();
        const int sp = (kb - 1) % ST;
        if (lane == 0) { mbar_arrive_cluster(bars + 8 * (ST + sp), 0); mbar_arrive_cluster(bars + 8 * (ST + sp), 1); }
      }
    }
    wg_wait<0>();
    fence_regs(acc[0]); fence_regs(acc[1]);
    if (tid == 0) TS(1, 1);
    named_bar_sync(1, 256);

#pragma unroll
    for (int mb = 0; mb < 2; mb++) {
#pragma unroll
      for (int h = 0; h < 2; h++) {
        const int r = wg * 128 + mb * 64 + w4 * 16 + g + h * 8;
#pragma unroll
        for (int j = 0; j < 8; j++) {
          const uint32_t off = r * 128 + ((j ^ (r & 7)) << 4) + t * 4;
          const float k0 = acc[mb][4 * (8 + j) + 2 * h], k1v = acc[mb][4 * (8 + j) + 2 * h + 1];
          const float v0 = acc[mb][4 * (16 + j) + 2 * h], v1 = acc[mb][4 * (16 + j) + 2 * h + 1];
          *reinterpret_cast<uint32_t*>(sgen + OFF_PK + off) = phi2(k0, k1v);
          *reinterpret_cast<uint32_t*>(sgen + OFF_V + off) = pack2(v0, v1);
        }
      }
    }
    if (tid < 256) *reinterpret_cast<uint32_t*>(sgen + OFF_ONES + tid * 4) = 0x3F803F80u;
    fence_async_smem();
    named_bar_sync(1, 256);

    if (tid == 0) TS(1, 2);
    float* part = g_part + (size_t)(hp * 8 + mt) * 2112;
    {
      float kv[32], zz[4];
#pragma unroll
      for (int i = 0; i < 32; i++) kv[i] = 0.f;
#pragma unroll
      for (int i = 0; i < 4; i++) zz[i] = 0.f;
      wg_fence();
#pragma unroll
      for (int ks = 0; ks < 8; ks++) {
        const uint64_t da = make_desc(sbase + OFF_PK + wg * 16384 + ks * 2048, 16, 1024);
        const uint64_t db = make_desc(sbase + OFF_V + wg * 16384 + ks * 2048, 16, 1024);
        const uint64_t d1 = make_desc(sbase + OFF_ONES, 16, 0);
        wgmma_ss_n64_tatb(kv, da, db, 1);
        wgmma_ss_n8_tatb(zz, da, d1, 1);
      }
      wg_commit();
      wg_wait<0>();
      fence_regs(kv); fence_regs(zz);
      const int hh = w4 >> 1;
      float* red = reinterpret_cast<float*>(sgen + OFF_RED);
      float vals[2][4][2];
#pragma unroll
      for (int h = 0; h < 2; h++)
#pragma unroll
        for (int j = 0; j < 4; j++) {
          vals[h][j][0] = hh ? kv[4 * (4 + j) + 2 * h] : kv[4 * j + 2 * h];
          vals[h][j][1] = hh ? kv[4 * (4 + j) + 2 * h + 1] : kv[4 * j + 2 * h + 1];
        }
      if (wg == 1) {
#pragma unroll
        for (int h = 0; h < 2; h++) {
          const int d = (w4 & 1) * 16 + g + h * 8;
#pragma unroll
          for (int j = 0; j < 4; j++)
            *reinterpret_cast<float2*>(red + hh * 1056 + d * 32 + 8 * j + 2 * t) = make_float2(vals[h][j][0], vals[h][j][1]);
          if (t == 0) red[hh * 1056 + 1024 + d] = zz[2 * h];
        }
      }
      named_bar_sync(1, 256);
      if (wg == 0) {
#pragma unroll
        for (int h = 0; h < 2; h++) {
          const int d = (w4 & 1) * 16 + g + h * 8;
#pragma unroll
          for (int j = 0; j < 4; j++) {
            const float2 o = *reinterpret_cast<const float2*>(red + hh * 1056 + d * 32 + 8 * j + 2 * t);
            *reinterpret_cast<float2*>(part + hh * 1056 + d * 32 + 8 * j + 2 * t) = make_float2(vals[h][j][0] + o.x, vals[h][j][1] + o.y);
          }
          if (t == 0) part[hh * 1056 + 1024 + d] = zz[2 * h] + red[hh * 1056 + 1024 + d];
        }
        __threadfence();
        named_bar_sync(2, 128);
        if (tid == 0) atomicAdd(&g_cnt[hp], 1u);
      }
    }
    if (tid == 0) TS(1, 3);
    uint32_t pq[2][4][4];
#pragma unroll
    for (int mb = 0; mb < 2; mb++)
#pragma unroll
      for (int kk = 0; kk < 4; kk++) {
        pq[mb][kk][0] = phi2(acc[mb][8 * kk + 0], acc[mb][8 * kk + 1]);
        pq[mb][kk][1] = phi2(acc[mb][8 * kk + 2], acc[mb][8 * kk + 3]);
        pq[mb][kk][2] = phi2(acc[mb][8 * kk + 4], acc[mb][8 * kk + 5]);
        pq[mb][kk][3] = phi2(acc[mb][8 * kk + 6], acc[mb][8 * kk + 7]);
      }
    if (tid == 0) TS(1, 4);
    if (tid == 0) {
      unsigned int v;
      do { asm volatile("ld.acquire.gpu.global.u32 %0, [%1];" : "=r"(v) : "l"(&g_cnt[hp]) : "memory"); } while (v < 8u);
    }
    named_bar_sync(1, 256);
    {
      if (tid == 0) TS(1, 5);
      const float* pb = g_part + (size_t)(hp * 8) * 2112;
      for (int i = tid; i < 528; i += 256) {
        float4 s4 = make_float4(0.f, 0.f, 0.f, 0.f);
#pragma unroll
        for (int p = 0; p < 8; p++) {
          float4 v4 = __ldcg(reinterpret_cast<const float4*>(pb + p * 2112) + i);
          s4.x += v4.x; s4.y += v4.y; s4.z += v4.z; s4.w += v4.w;
        }
        const int hh = i / 264, rem = i - hh * 264;
        uint8_t* tile = sgen + OFF_KV + hh * 4096;
        if (rem < 256) {
          const int d = rem >> 3, e = (rem & 7) * 4;
          const uint32_t off = d * 128 + (((e >> 3) ^ (d & 7)) << 4) + (e & 7) * 2;
          *reinterpret_cast<uint2*>(tile + off) = make_uint2(pack2(s4.x, s4.y), pack2(s4.z, s4.w));
        } else {
          const int d0 = (rem - 256) * 4;
          float zv[4] = {s4.x, s4.y, s4.z, s4.w};
#pragma unroll
          for (int q = 0; q < 4; q++) {
            const int d = d0 + q;
            const uint32_t off = d * 128 + ((4 ^ (d & 7)) << 4);
            *reinterpret_cast<uint4*>(tile + off) = make_uint4(pack2(zv[q], 0.f), 0u, 0u, 0u);
          }
        }
      }
    }
    fence_async_smem();
    named_bar_sync(1, 256);
    if (tid == 0) TS(1, 6);
#pragma unroll
    for (int mb = 0; mb < 2; mb++) {
#pragma unroll
      for (int hh = 0; hh < 2; hh++) {
        float num[20];
#pragma unroll
        for (int i = 0; i < 20; i++) num[i] = 0.f;
        wg_fence();
#pragma unroll
        for (int kk = 0; kk < 2; kk++) {
          const uint64_t db = make_desc(sbase + OFF_KV + hh * 4096 + kk * 2048, 16, 1024);
          wgmma_rs_n40_tb(num, pq[mb][hh * 2 + kk][0], pq[mb][hh * 2 + kk][1], pq[mb][hh * 2 + kk][2], pq[mb][hh * 2 + kk][3], db, 1);
        }
        wg_commit();
        wg_wait<0>();
        fence_regs(num);
#pragma unroll
        for (int h = 0; h < 2; h++) {
          float den = __shfl_sync(0xffffffffu, num[16 + 2 * h], lane & ~3);
          den = bfr(bfr(den) + 1e-6f);
          const float rden = 1.0f / den;
          const int r = wg * 128 + mb * 64 + w4 * 16 + g + h * 8;
#pragma unroll
          for (int j = 0; j < 4; j++) {
            const uint32_t n2 = pack2(num[4 * j + 2 * h], num[4 * j + 2 * h + 1]);
            const float o0 = lo_f(n2) * rden, o1 = hi_f(n2) * rden;
            const uint32_t off = r * 128 + (((hh * 4 + j) ^ (r & 7)) << 4) + t * 4;
            *reinterpret_cast<uint32_t*>(sgen + OFF_O + off) = pack2(o0, o1);
          }
        }
      }
    }
    named_bar_sync(1, 256);
    if (tid == 0) TS(1, 7);
    for (int i = tid; i < 256 * 8; i += 256) {
      const int r = i >> 3, c = i & 7;
      uint4 v = *reinterpret_cast<const uint4*>(sgen + OFF_O + r * 128 + ((c ^ (r & 7)) << 4));
      *reinterpret_cast<uint4*>(g_o + (size_t)(m0 + r) * DM + hp * 64 + c * 8) = v;
    }
    if (tid == 0) TS(1, 8);
    cluster_sync_all();
  }
}

namespace k3 {
constexpr int BM = 128, BN = 128, BK = 64, ST = 5;
constexpr int A_BYTES = BM * BK * 2, B_BYTES = BK * BN * 2, STAGE = A_BYTES + B_BYTES;
constexpr int OFF_BT = ST * STAGE;
constexpr int OFF_BAR = OFF_BT + 32768;
constexpr int SMEM = OFF_BAR + 1024 + 256;
}

__global__ void __cluster_dims__(2, 1, 1) __launch_bounds__(384, 1)
k3_out(const __grid_constant__ CUtensorMap tmo, const __grid_constant__ CUtensorMap tmw,
       const __grid_constant__ CUtensorMap tmbt, const __grid_constant__ CUtensorMap tmout) {
  using namespace k3;
  extern __shared__ uint8_t smem_raw[];
  const uint32_t sbase = (smem_u32(smem_raw) + 1023) & ~1023u;
  uint8_t* sgen = smem_raw + (sbase - smem_u32(smem_raw));
  const uint32_t bars = sbase + OFF_BAR;
  const uint32_t barbt = bars + 8 * 2 * ST;
  const int tid = threadIdx.x, warp = tid >> 5, lane = tid & 31;
  const uint32_t rank = cluster_ctarank();
  const int cl = blockIdx.x >> 1;
  const int mt = cl >> 2;
  const int nt = ((cl & 3) << 1) + rank;
  const int m0 = mt * BM, n0 = nt * BN;

  if (tid == 0) {
    for (int s = 0; s < ST; s++) {
      mbar_init(bars + 8 * s, 1);
      mbar_init(bars + 8 * (ST + s), 16);
    }
    mbar_init(barbt, 1);
    asm volatile("fence.mbarrier_init.release.cluster;" ::: "memory");
  }
  cluster_sync_all();

  if (warp >= 8) {
    asm volatile("setmaxnreg.dec.sync.aligned.u32 40;");
    if (warp == 8 && lane == 0) {
      for (int kb = 0; kb < ST; kb++) {
        const uint32_t full = bars + 8 * kb;
        mbar_expect_tx(full, STAGE);
        const uint32_t sb = sbase + kb * STAGE + A_BYTES;
#pragma unroll
        for (int j = 0; j < 2; j++) tma_load_2d(sb + j * 8192, &tmw, full, n0 + j * 64, kb * BK);
      }
      pdl_wait();
      if (blockIdx.x == 0) for (int i = 0; i < 16; i++) g_cnt[i] = 0;
      for (int kb = 0; kb < DM / BK; kb++) {
        const int s = kb % ST;
        const uint32_t full = bars + 8 * s;
        const uint32_t sa = sbase + s * STAGE, sb = sa + A_BYTES;
        if (kb >= ST) {
          mbar_wait(bars + 8 * (ST + s), ((kb / ST) & 1) ^ 1);
          mbar_expect_tx(full, STAGE);
#pragma unroll
          for (int j = 0; j < 2; j++) tma_load_2d(sb + j * 8192, &tmw, full, n0 + j * 64, kb * BK);
        }
        tma_load_2d_mc(sa + rank * 8192, &tmo, full, kb * BK, m0 + rank * 64, (uint16_t)3);
        if (kb == 2) {
          mbar_expect_tx(barbt, 32768);
          tma_load_2d(sbase + OFF_BT, &tmbt, barbt, m0, n0);
          tma_load_2d(sbase + OFF_BT + 16384, &tmbt, barbt, m0 + 64, n0);
        }
      }
    }
    cluster_sync_all();
  } else {
    asm volatile("setmaxnreg.inc.sync.aligned.u32 232;");
    const int wg = warp >> 2, w4 = warp & 3, g = lane >> 2, t = lane & 3;
    if (tid == 0) TS(3, 0);
    float acc[64];
#pragma unroll
    for (int i = 0; i < 64; i++) acc[i] = 0.f;
    for (int kb = 0; kb < DM / BK; kb++) {
      const int s = kb % ST;
      mbar_wait(bars + 8 * s, (kb / ST) & 1);
      const uint32_t sa = sbase + s * STAGE + wg * 8192, sb = sbase + s * STAGE + A_BYTES;
      wg_fence();
#pragma unroll
      for (int ks = 0; ks < 4; ks++) {
        const uint64_t db = make_desc(sb + ks * 2048, 8192, 1024);
        const uint64_t da = make_desc(sa + ks * 32, 16, 1024);
        wgmma_ss_n128_tb(acc, da, db, 1);
      }
      wg_commit();
      if (kb > 0) {
        wg_wait<1>();
        const int sp = (kb - 1) % ST;
        if (lane == 0) { mbar_arrive_cluster(bars + 8 * (ST + sp), 0); mbar_arrive_cluster(bars + 8 * (ST + sp), 1); }
      }
    }
    wg_wait<0>();
    fence_regs(acc);
    if (tid == 0) TS(3, 1);
    named_bar_sync(1, 256);
    mbar_wait(barbt, 0);
    pdl_wait();
#pragma unroll
    for (int h = 0; h < 2; h++) {
      const int rl = wg * 64 + w4 * 16 + g + h * 8;
      const float gt = g_gate[m0 + rl];
      const float omg = bfr(1.0f - gt);
      const uint8_t* bt = sgen + OFF_BT + wg * 16384;
      const int ll = rl & 63;
#pragma unroll
      for (int j = 0; j < 16; j++) {
        const int c = 8 * j + 2 * t;
        const float b0 = __bfloat162float(*reinterpret_cast<const bf16*>(bt + c * 128 + (((ll >> 3) ^ (c & 7)) << 4) + (ll & 7) * 2));
        const float b1 = __bfloat162float(*reinterpret_cast<const bf16*>(bt + (c + 1) * 128 + (((ll >> 3) ^ ((c + 1) & 7)) << 4) + (ll & 7) * 2));
        const uint32_t a2 = pack2(acc[4 * j + 2 * h], acc[4 * j + 2 * h + 1]);
        const float o0 = bfr(gt * lo_f(a2)) + bfr(omg * b0);
        const float o1 = bfr(gt * hi_f(a2)) + bfr(omg * b1);
        *reinterpret_cast<uint32_t*>(sgen + (j >> 3) * 16384 + rl * 128 + (((j & 7) ^ (rl & 7)) << 4) + t * 4) = pack2(o0, o1);
      }
    }
    fence_async_smem();
    if (tid == 0) TS(3, 2);
    named_bar_sync(2 + wg, 128);
    if ((tid & 127) == 0) {
#pragma unroll
      for (int j = 0; j < 2; j++)
        asm volatile("cp.async.bulk.tensor.2d.global.shared::cta.bulk_group [%0, {%2, %3}], [%1];" ::"l"(&tmout),
                     "r"(sbase + j * 16384 + wg * 8192), "r"(n0 + j * 64), "r"(m0 + wg * 64) : "memory");
      asm volatile("cp.async.bulk.commit_group;" ::: "memory");
      asm volatile("cp.async.bulk.wait_group.read 0;" ::: "memory");
      if (tid == 0) TS(3, 3);
    }
    cluster_sync_all();
  }
}

__device__ __align__(1024) bf16 g_bT[DM * SEQ];
constexpr int KOFF = 2048 + 16;
constexpr int KSZ = 2112;
constexpr int KCH = 2 * KSZ + 16;

__device__ __forceinline__ void mma_bf16(float (&d)[4], uint32_t a0, uint32_t a1, uint32_t a2, uint32_t a3, uint32_t b0, uint32_t b1) {
  asm volatile("mma.sync.aligned.m16n8k16.row.col.f32.bf16.bf16.f32 {%0,%1,%2,%3}, {%4,%5,%6,%7}, {%8,%9}, {%0,%1,%2,%3};"
               : "+f"(d[0]), "+f"(d[1]), "+f"(d[2]), "+f"(d[3]) : "r"(a0), "r"(a1), "r"(a2), "r"(a3), "r"(b0), "r"(b1));
}
__device__ __forceinline__ void mma_f16(float (&d)[4], uint32_t a0, uint32_t a1, uint32_t a2, uint32_t a3, uint32_t b0, uint32_t b1) {
  asm volatile("mma.sync.aligned.m16n8k16.row.col.f32.f16.f16.f32 {%0,%1,%2,%3}, {%4,%5,%6,%7}, {%8,%9}, {%0,%1,%2,%3};"
               : "+f"(d[0]), "+f"(d[1]), "+f"(d[2]), "+f"(d[3]) : "r"(a0), "r"(a1), "r"(a2), "r"(a3), "r"(b0), "r"(b1));
}
struct cf { float r, i; };
__device__ __forceinline__ cf cmul(cf a, cf b) { cf c; c.r = a.r * b.r - a.i * b.i; c.i = a.r * b.i + a.i * b.r; return c; }
__device__ __forceinline__ cf csq(cf a) { cf c; c.r = a.r * a.r - a.i * a.i; c.i = 2.f * a.r * a.i; return c; }
__device__ __forceinline__ cf cexpp(float ar, float ai, float p) {
  const float e = ex2f(ar * p * 1.4426950408889634f);
  const float th = ai * p;
  const float k = rintf(th * 0.15915494309189535f);
  float r = fmaf(k, -6.2831854820251465f, th);
  r = fmaf(k, 1.7484556000744e-7f, r);
  cf w; w.r = e * __cosf(r); w.i = e * __sinf(r); return w;
}
__device__ __forceinline__ uint32_t packh(float lo, float hi) {
  uint32_t r; asm("cvt.rn.f16x2.f32 %0, %1, %2;" : "=r"(r) : "f"(hi), "f"(lo)); return r;
}

namespace k2 {
constexpr int CH = 8;
constexpr int UPAD = 128;
constexpr int USZ = UPAD + SEQ;
constexpr int TSTR = 40;
constexpr int TABW = 72 * TSTR;
constexpr int PAIRW = 2 * TABW;
constexpr int P_K = 0;
constexpr int P_Q = KCH / 2;
constexpr int P_B = P_Q + 2 * 648;
constexpr int P_R = P_B + 324 + 4;
constexpr int OFF_U = 0;
constexpr int OFF_P = OFF_U + CH * USZ * 2;
constexpr int PW2 = P_R + 2048;
constexpr int SMEM = OFF_P + CH * PW2 * 4;
static_assert(PW2 >= PAIRW && (P_R % 4) == 0 && (PW2 % 4) == 0, "layout");
}

__global__ void __launch_bounds__(512, 1)
k2_ssm(const bf16* __restrict__ x, const bf16* __restrict__ logAr, const bf16* __restrict__ Aim, const bf16* __restrict__ Cre,
       const bf16* __restrict__ Cim, const bf16* __restrict__ logdt, const bf16* __restrict__ Dskip) {
  using namespace k2;
  extern __shared__ __align__(16) uint8_t sm[];
  const int tid = threadIdx.x, warp = tid >> 5, lane = tid & 31, g = lane >> 2, t = lane & 3;
  const int ch = warp >> 1, half = warp & 1, l64 = half * 32 + lane;
  const int d0 = blockIdx.x * CH;
  bf16* us = reinterpret_cast<bf16*>(sm + OFF_U);
  uint32_t* pw = reinterpret_cast<uint32_t*>(sm + OFF_P) + ch * PW2;
  if (tid == 0) TS(2, 0);
  pdl_launch();

  const int d = d0 + ch;
  bf16 p_la[2], p_ai[2], p_cr[2], p_ci[2];
#pragma unroll
  for (int c = 0; c < 2; c++) {
    const int idx = d * NMODE + half * 64 + c * 32 + lane;
    p_la[c] = logAr[idx]; p_ai[c] = Aim[idx]; p_cr[c] = Cre[idx]; p_ci[c] = Cim[idx];
  }
  const bf16 p_dt = logdt[d];
  asm volatile("" ::: "memory");
  uint4 uv[2][2];
#pragma unroll
  for (int it = 0; it < 2; it++) {
    const int l = 2 * (tid + it * 512);
    uv[it][0] = __ldg(reinterpret_cast<const uint4*>(x + (size_t)l * DM + d0));
    uv[it][1] = __ldg(reinterpret_cast<const uint4*>(x + (size_t)(l + 1) * DM + d0));
  }

  float acc[5][4];
#pragma unroll
  for (int a = 0; a < 5; a++)
#pragma unroll
    for (int b = 0; b < 4; b++) acc[a][b] = 0.f;
  float last = 0.f, scale;
  {
    const float dt = bfr(ex2f(__bfloat162float(p_dt) * 1.4426950408889634f));
    float cr[2], ci[2], arr[2], aii[2];
#pragma unroll
    for (int c = 0; c < 2; c++) {
      arr[c] = -bfr(ex2f(__bfloat162float(p_la[c]) * 1.4426950408889634f)) * dt;
      aii[c] = __bfloat162float(p_ai[c]) * dt;
      cr[c] = __bfloat162float(p_cr[c]) * dt;
      ci[c] = __bfloat162float(p_ci[c]) * dt;
    }
    float mx = fmaxf(fmaxf(fabsf(cr[0]), fabsf(ci[0])), fmaxf(fabsf(cr[1]), fabsf(ci[1])));
#pragma unroll
    for (int o = 16; o; o >>= 1) mx = fmaxf(mx, __shfl_xor_sync(0xffffffffu, mx, o));
    {
      int e = (int)((__float_as_uint(mx) >> 23) & 255u) + 1;
      e = e < 32 ? 32 : (e > 220 ? 220 : e);
      scale = __uint_as_float((uint32_t)e << 23);
    }
    const float iscale = __uint_as_float((uint32_t)(254 - ((__float_as_uint(scale) >> 23) & 255u)) << 23);
    uint32_t* tab = pw + half * TABW;
    if (tid == 0) TS(2, 5);
#pragma unroll 1
    for (int c = 0; c < 2; c++) {
      const float ar = arr[c], ai = aii[c];
      cf C; C.r = cr[c] * iscale; C.i = ci[c] * iscale;
      const cf W1 = cexpp(ar, ai, 1.f), W16 = cexpp(ar, ai, 16.f), W256 = cexpp(ar, ai, 256.f);
      const cf W512 = csq(W256), W1024 = csq(W512);
      const cf W1536 = cmul(W1024, W512);
      {
        const cf w2048 = csq(W1024);
        last += cr[c] * w2048.r - ci[c] * w2048.i;
      }
      uint32_t* tp = tab + lane;
      {
        cf xa = C;
#pragma unroll
        for (int i = 0; i < 16; i++) {
          const uint32_t pk = packh(xa.r, -xa.i);
          tp[i * TSTR] = pk;
          if ((i & 1) == 0) {
            tp[(16 + i / 2) * TSTR] = pk;
            const cf xb = cmul(xa, W256);
            tp[(24 + i / 2) * TSTR] = packh(xb.r, -xb.i);
          }
          xa = cmul(xa, W16);
        }
      }
      {
        cf y; y.r = 1.f; y.i = 0.f;
        const cf W528 = cmul(W512, W16);
        const cf WA16 = cmul(W1024, W16), WB16 = cmul(W1536, W16);
#pragma unroll
        for (int j = 0; j < 16; j++) {
          tp[(32 + j) * TSTR] = packh(y.r, y.i);
          if ((j & 1) == 0) { const cf z = cmul(y, W256); tp[(48 + j / 2) * TSTR] = packh(z.r, z.i); }
          if ((j & 3) == 0) {
            const cf z0 = cmul(y, W512), z1 = cmul(y, W528);
            tp[(56 + j / 4) * TSTR] = packh(z0.r, z0.i);
            tp[(60 + j / 4) * TSTR] = packh(z1.r, z1.i);
          }
          if ((j & 7) == 0) {
            const cf z0 = cmul(y, W1024), z1 = cmul(y, WA16), z2 = cmul(y, W1536), z3 = cmul(y, WB16);
            tp[(64 + j / 8) * TSTR] = packh(z0.r, z0.i);
            tp[(66 + j / 8) * TSTR] = packh(z1.r, z1.i);
            tp[(68 + j / 8) * TSTR] = packh(z2.r, z2.i);
            tp[(70 + j / 8) * TSTR] = packh(z3.r, z3.i);
          }
          y = cmul(y, W1);
        }
      }
      __syncwarp();
      if (tid == 0) TS(2, 6 + 2 * c);
#pragma unroll
      for (int ks4 = 0; ks4 < 4; ks4++) {
        const uint32_t* fp = tab + 8 * ks4 + 2 * t;
        const uint2 xa0 = *reinterpret_cast<const uint2*>(fp + g * TSTR), xa1 = *reinterpret_cast<const uint2*>(fp + (g + 8) * TSTR);
        const uint2 xb0 = *reinterpret_cast<const uint2*>(fp + (16 + g) * TSTR), xb1 = *reinterpret_cast<const uint2*>(fp + (24 + g) * TSTR);
        const uint2 y1 = *reinterpret_cast<const uint2*>(fp + (32 + g) * TSTR), y2 = *reinterpret_cast<const uint2*>(fp + (40 + g) * TSTR);
        const uint2 y3 = *reinterpret_cast<const uint2*>(fp + (48 + g) * TSTR), y4 = *reinterpret_cast<const uint2*>(fp + (56 + g) * TSTR);
        const uint2 y5 = *reinterpret_cast<const uint2*>(fp + (64 + g) * TSTR);
        mma_f16(acc[0], xa0.x, xa1.x, xa0.y, xa1.y, y1.x, y1.y);
        mma_f16(acc[1], xa0.x, xa1.x, xa0.y, xa1.y, y2.x, y2.y);
        mma_f16(acc[2], xa0.x, xa1.x, xa0.y, xa1.y, y3.x, y3.y);
        mma_f16(acc[3], xb0.x, xb1.x, xb0.y, xb1.y, y4.x, y4.y);
        mma_f16(acc[4], xb0.x, xb1.x, xb0.y, xb1.y, y5.x, y5.y);
      }
      __syncwarp();
      if (tid == 0) TS(2, 7 + 2 * c);
    }
  }
  if (tid == 0) TS(2, 1);
  if (tid < CH * UPAD / 2) {
    const int c = tid / (UPAD / 2), o = tid % (UPAD / 2);
    reinterpret_cast<uint32_t*>(us + c * USZ)[o] = 0u;
  }
#pragma unroll
  for (int it = 0; it < 2; it++) {
    const int l = 2 * (tid + it * 512);
    const int e = l & 15;
    const int pe = ((e & 7) >> 1) * 4 + (e >> 3) * 2;
    const int pos = UPAD + (l & ~15) + pe;
    const uint32_t a[4] = {uv[it][0].x, uv[it][0].y, uv[it][0].z, uv[it][0].w};
    const uint32_t b[4] = {uv[it][1].x, uv[it][1].y, uv[it][1].z, uv[it][1].w};
#pragma unroll
    for (int c = 0; c < 4; c++) {
      *reinterpret_cast<uint32_t*>(us + (2 * c) * USZ + pos) = __byte_perm(a[c], b[c], 0x5410);
      *reinterpret_cast<uint32_t*>(us + (2 * c + 1) * USZ + pos) = __byte_perm(a[c], b[c], 0x7632);
    }
  }
  named_bar_sync(1 + ch, 64);
  if (tid == 0) TS(2, 10);
  float* kqp = reinterpret_cast<float*>(pw + P_Q);
  {
    float* kq = kqp + half * 648;
    const float sc2 = 2.f * scale;
#pragma unroll
    for (int h = 0; h < 2; h++) {
      const int i = g + 8 * h;
      *reinterpret_cast<float2*>(kq + 16 * i + 2 * t) = make_float2(sc2 * acc[0][2 * h], sc2 * acc[0][2 * h + 1]);
      *reinterpret_cast<float2*>(kq + 16 * i + 8 + 2 * t) = make_float2(sc2 * acc[1][2 * h], sc2 * acc[1][2 * h + 1]);
      *reinterpret_cast<float2*>(kq + 256 + 8 * i + 2 * t) = make_float2(sc2 * acc[2][2 * h], sc2 * acc[2][2 * h + 1]);
      *reinterpret_cast<float2*>(kq + 384 + 8 * i + 2 * t) = make_float2(sc2 * acc[3][2 * h], sc2 * acc[3][2 * h + 1]);
      *reinterpret_cast<float2*>(kq + 512 + 4 * i + 64 * (t >> 1) + 2 * (t & 1)) = make_float2(sc2 * acc[4][2 * h], sc2 * acc[4][2 * h + 1]);
    }
#pragma unroll
    for (int o = 16; o; o >>= 1) last += __shfl_xor_sync(0xffffffffu, last, o);
    if (lane == 0) kq[640] = 2.f * last;
  }
  named_bar_sync(1 + ch, 64);
  if (tid == 0) TS(2, 11);
  bf16* kb = reinterpret_cast<bf16*>(pw + P_B);
  for (int i = l64; i < 324; i += 64) {
    const float2 a = *reinterpret_cast<const float2*>(kqp + 2 * i), b = *reinterpret_cast<const float2*>(kqp + 648 + 2 * i);
    pw[P_B + i] = pack2(a.x + b.x, a.y + b.y);
  }
  named_bar_sync(1 + ch, 64);
  {
    if (tid == 0) TS(2, 12);
    const uint16_t* kh = reinterpret_cast<const uint16_t*>(kb);
    for (int v = l64; v < KSZ / 8; v += 64) {
      uint32_t kv[9];
      const int xt = KOFF - 8 * v;
      if (xt > 2048 || xt < 0) {
#pragma unroll
        for (int q = 0; q < 9; q++) kv[q] = 0u;
      } else if (xt > 1024) {
        const int m = xt >> 3;
        const uint32_t A = kh[384 + m], B = kh[383 + m], T = (m & 1) ? B : A;
        kv[0] = A; kv[1] = A; kv[2] = A; kv[3] = A; kv[4] = T; kv[5] = B; kv[6] = B; kv[7] = B; kv[8] = B;
      } else if (xt > 512) {
        const int m = xt >> 2;
        const uint32_t A = kh[256 + m], B = kh[255 + m], C = kh[254 + m];
        kv[0] = A; kv[1] = A; kv[2] = A; kv[3] = B; kv[4] = B; kv[5] = B; kv[6] = C; kv[7] = C; kv[8] = C;
      } else if (xt > 256) {
        const int m = xt >> 1;
        const uint32_t A = kh[128 + m], B = kh[127 + m], C = kh[126 + m], E = kh[125 + m], F4 = kh[124 + m];
        kv[0] = A; kv[1] = A; kv[2] = B; kv[3] = C; kv[4] = C; kv[5] = C; kv[6] = E; kv[7] = F4; kv[8] = F4;
      } else {
#pragma unroll
        for (int q = 0; q < 9; q++) kv[q] = xt - q >= 0 ? (uint32_t)kh[xt - q] : 0u;
      }
      *reinterpret_cast<uint4*>(pw + P_K + 4 * v) =
          make_uint4(kv[0] | (kv[1] << 16), kv[2] | (kv[3] << 16), kv[4] | (kv[5] << 16), kv[6] | (kv[7] << 16));
      *reinterpret_cast<uint4*>(pw + P_K + (KSZ + 16) / 2 + 4 * v) =
          make_uint4(kv[1] | (kv[2] << 16), kv[3] | (kv[4] << 16), kv[5] | (kv[6] << 16), kv[7] | (kv[8] << 16));
    }
  }
  if (tid == 0) TS(2, 13);
  __syncthreads();
  if (tid == 0) TS(2, 2);

  float D[16][4];
#pragma unroll
  for (int j = 0; j < 16; j++)
#pragma unroll
    for (int q = 0; q < 4; q++) D[j][q] = 0.f;
  const bf16* uc = us + ch * USZ + UPAD;
  {
    const uint32_t* fbase = pw + P_K + ((g & 1) ? (KSZ + 16) / 2 : 0) + ((KOFF - g + 2 * t) >> 1);
    for (int r = half * 4; r < half * 4 + 4; r++) {
      uint32_t B[16][2];
#pragma unroll
      for (int j = 0; j < 16; j++) {
        const uint2 v = *reinterpret_cast<const uint2*>(uc + 16 * (8 * j - r + g) + 4 * t);
        B[j][0] = v.x; B[j][1] = v.y;
      }
      uint32_t fm1 = fbase[-4 * (2 * r - 1)];
#pragma unroll
      for (int k = 0; k < 16; k++) {
        const int dl = 8 * k + r;
        const uint32_t f0 = fbase[-4 * (2 * dl)];
        const uint32_t f1 = fbase[-4 * (2 * dl + 1)];
        if (k > 0) fm1 = fbase[-4 * (2 * dl - 1)];
#pragma unroll
        for (int j = k; j < 16; j++) mma_bf16(D[j], f0, f1, fm1, f0, B[j - k][0], B[j - k][1]);
      }
    }
  }
  if (tid == 0) TS(2, 3);
  float* red = reinterpret_cast<float*>(pw + P_R);
#pragma unroll
  for (int j = 0; j < 8; j++) {
    const int jo = half ? j : j + 8;
    *reinterpret_cast<float4*>(red + (jo * 32 + lane) * 4) =
        make_float4(half ? D[j][0] : D[j + 8][0], half ? D[j][1] : D[j + 8][1], half ? D[j][2] : D[j + 8][2], half ? D[j][3] : D[j + 8][3]);
  }
  named_bar_sync(1 + ch, 64);
  {
    const float dsk = __bfloat162float(Dskip[d]);
    uint16_t* ys = reinterpret_cast<uint16_t*>(pw + P_K);
#pragma unroll
    for (int j = 0; j < 8; j++) {
      const int jm = half ? j + 8 : j;
      const float4 o = *reinterpret_cast<const float4*>(red + (jm * 32 + lane) * 4);
      const float dd[4] = {(half ? D[j + 8][0] : D[j][0]) + o.x, (half ? D[j + 8][1] : D[j][1]) + o.y,
                           (half ? D[j + 8][2] : D[j][2]) + o.z, (half ? D[j + 8][3] : D[j][3]) + o.w};
#pragma unroll
      for (int q = 0; q < 4; q++) {
        const int a = 8 * jm + 2 * t + (q & 1), bb = g + (q >> 1) * 8;
        const int pe = ((bb & 7) >> 1) * 4 + (bb >> 3) * 2 + (bb & 1);
        const float uvv = __bfloat162float(uc[16 * a + pe]);
        const float y = bfr(dd[q]) + bfr(uvv * dsk);
        ys[16 * a + bb] = (uint16_t)(__float_as_uint(bfr(y)) >> 16);
      }
    }
    __syncwarp();
    bf16* dst = g_bT + (size_t)d * SEQ + half * 1024;
#pragma unroll
    for (int i = 0; i < 4; i++) {
      const uint4 v = *reinterpret_cast<const uint4*>(ys + half * 1024 + (i * 32 + lane) * 8);
      *reinterpret_cast<uint4*>(dst + (i * 32 + lane) * 8) = v;
    }
  }
  if (tid == 0) TS(2, 4);
  if (tid == 0) pdl_wait();
}

typedef CUresult (*EncodeFn)(CUtensorMap*, CUtensorMapDataType, cuuint32_t, void*, const cuuint64_t*, const cuuint64_t*,
                             const cuuint32_t*, const cuuint32_t*, CUtensorMapInterleave, CUtensorMapSwizzle,
                             CUtensorMapL2promotion, CUtensorMapFloatOOBfill);

static void make_map(EncodeFn enc, CUtensorMap* m, void* ptr, uint64_t inner, uint64_t outer, uint32_t bi, uint32_t bo) {
  cuuint64_t dims[2] = {inner, outer};
  cuuint64_t strides[1] = {inner * 2};
  cuuint32_t box[2] = {bi, bo};
  cuuint32_t es[2] = {1, 1};
  enc(m, CU_TENSOR_MAP_DATA_TYPE_BFLOAT16, 2, ptr, dims, strides, box, es, CU_TENSOR_MAP_INTERLEAVE_NONE,
      CU_TENSOR_MAP_SWIZZLE_128B, CU_TENSOR_MAP_L2_PROMOTION_L2_256B, CU_TENSOR_MAP_FLOAT_OOB_FILL_NONE);
}

extern "C" void kernel_launch(void* const* d_in, const int* in_sizes, int n_in, void* d_out, int out_size) {
  const bf16* x = (const bf16*)d_in[0];
  const bf16* wqkv = (const bf16*)d_in[1];
  const bf16* wo = (const bf16*)d_in[2];
  const bf16* logAr = (const bf16*)d_in[4];
  const bf16* Aim = (const bf16*)d_in[5];
  const bf16* Cre = (const bf16*)d_in[6];
  const bf16* Cim = (const bf16*)d_in[7];
  const bf16* logdt = (const bf16*)d_in[8];
  const bf16* Dskip = (const bf16*)d_in[9];
  const bf16* gatew = (const bf16*)d_in[10];

  static EncodeFn enc = nullptr;
  static void* p_o = nullptr;
  static void* p_bT = nullptr;
  if (!enc) {
    void* fn = nullptr;
    cudaDriverEntryPointQueryResult qr;
    cudaGetDriverEntryPoint("cuTensorMapEncodeTiled", &fn, cudaEnableDefault, &qr);
    enc = (EncodeFn)fn;
    cudaGetSymbolAddress(&p_o, g_o);
    cudaGetSymbolAddress(&p_bT, g_bT);
    cudaFuncSetAttribute(k1_qkv_attn, cudaFuncAttributeMaxDynamicSharedMemorySize, k1::SMEM);
    cudaFuncSetAttribute(k2_ssm, cudaFuncAttributeMaxDynamicSharedMemorySize, k2::SMEM);
    cudaFuncSetAttribute(k3_out, cudaFuncAttributeMaxDynamicSharedMemorySize, k3::SMEM);
  }
  CUtensorMap tmx, tmw, tmo, tmwo, tmbt, tmout;
  make_map(enc, &tmx, (void*)x, 1024, 2048, 64, 128);
  make_map(enc, &tmw, (void*)wqkv, 3072, 1024, 64, 64);
  make_map(enc, &tmo, p_o, 1024, 2048, 64, 64);
  make_map(enc, &tmwo, (void*)wo, 1024, 1024, 64, 64);
  make_map(enc, &tmbt, p_bT, 2048, 1024, 64, 128);
  make_map(enc, &tmout, d_out, 1024, 2048, 64, 64);

  k1_qkv_attn<<<128, 384, k1::SMEM>>>(tmx, tmw, x, gatew, logAr, Aim, Cre, Cim);
  cudaLaunchAttribute at[1];
  at[0].id = cudaLaunchAttributeProgrammaticStreamSerialization;
  at[0].val.programmaticStreamSerializationAllowed = 1;
  cudaLaunchConfig_t cfg = {};
  cfg.stream = cudaStreamPerThread; cfg.attrs = at; cfg.numAttrs = 1;
  cfg.gridDim = dim3(128); cfg.blockDim = dim3(512); cfg.dynamicSmemBytes = k2::SMEM;
  cudaLaunchKernelEx(&cfg, k2_ssm, x, logAr, Aim, Cre, Cim, logdt, Dskip);
  cfg.blockDim = dim3(384); cfg.dynamicSmemBytes = k3::SMEM;
  cudaLaunchKernelEx(&cfg, k3_out, tmo, tmwo, tmbt, tmout);
}
```

```cpp
#include <cuda_runtime.h>
#include <cuda_bf16.h>
#include <cuda.h>
#include <stdint.h>

typedef __nv_bfloat16 bf16;

constexpr int SEQ = 2048, DM = 1024, NMODE = 128;

__device__ __align__(1024) bf16 g_o[SEQ * DM];
__device__ __align__(1024) bf16 g_b[SEQ * DM];
__device__ float g_gate[SEQ];
__device__ __align__(16) float g_part[16 * 8 * 2 * 1056];
__device__ unsigned int g_cnt[16];

#define TS(k, i) do {} while (0)
__device__ __forceinline__ uint32_t smem_u32(const void* p) { return (uint32_t)__cvta_generic_to_shared(p); }
__device__ __forceinline__ void mbar_init(uint32_t bar, uint32_t cnt) {
  asm volatile("mbarrier.init.shared::cta.b64 [%0], %1;" ::"r"(bar), "r"(cnt));
}
__device__ __forceinline__ void mbar_expect_tx(uint32_t bar, uint32_t bytes) {
  asm volatile("mbarrier.arrive.expect_tx.shared::cta.b64 _, [%0], %1;" ::"r"(bar), "r"(bytes) : "memory");
}
__device__ __forceinline__ void mbar_arrive_cluster(uint32_t bar, uint32_t cta) {
  asm volatile(
      "{\n.reg .b32 ra;\nmapa.shared::cluster.u32 ra, %0, %1;\n"
      "mbarrier.arrive.shared::cluster.b64 _, [ra];\n}\n" ::"r"(bar), "r"(cta) : "memory");
}
__device__ __forceinline__ bool mbar_try_wait(uint32_t bar, uint32_t parity) {
  uint32_t ok;
  asm volatile(
      "{\n.reg .pred p;\nmbarrier.try_wait.parity.shared::cta.b64 p, [%1], %2;\nselp.u32 %0, 1, 0, p;\n}\n"
      : "=r"(ok) : "r"(bar), "r"(parity) : "memory");
  return ok;
}
__device__ __forceinline__ void mbar_wait(uint32_t bar, uint32_t parity) {
  while (!mbar_try_wait(bar, parity)) {}
}
__device__ __forceinline__ void tma_load_2d(uint32_t dst, const CUtensorMap* map, uint32_t bar, int c0, int c1) {
  asm volatile(
      "cp.async.bulk.tensor.2d.shared::cluster.global.mbarrier::complete_tx::bytes [%0], [%1, {%3, %4}], [%2];" ::"r"(dst),
      "l"(map), "r"(bar), "r"(c0), "r"(c1) : "memory");
}
__device__ __forceinline__ void tma_load_2d_mc(uint32_t dst, const CUtensorMap* map, uint32_t bar, int c0, int c1,
                                               uint16_t mask) {
  asm volatile(
      "cp.async.bulk.tensor.2d.shared::cluster.global.mbarrier::complete_tx::bytes.multicast::cluster [%0], [%1, {%3, %4}], [%2], %5;" ::"r"(dst),
      "l"(map), "r"(bar), "r"(c0), "r"(c1), "h"(mask) : "memory");
}
__device__ __forceinline__ void cluster_sync_all() {
  asm volatile("barrier.cluster.arrive.release.aligned;\nbarrier.cluster.wait.acquire.aligned;\n" ::: "memory");
}
__device__ __forceinline__ uint32_t cluster_ctarank() {
  uint32_t r; asm volatile("mov.u32 %0, %%cluster_ctarank;" : "=r"(r)); return r;
}
__device__ __forceinline__ void pdl_wait() { asm volatile("griddepcontrol.wait;" ::: "memory"); }
__device__ __forceinline__ void pdl_launch() { asm volatile("griddepcontrol.launch_dependents;" ::: "memory"); }
__device__ __forceinline__ void named_bar_sync(int id, int n) { asm volatile("bar.sync %0, %1;" ::"r"(id), "r"(n) : "memory"); }
__device__ __forceinline__ void fence_async_smem() { asm volatile("fence.proxy.async.shared::cta;" ::: "memory"); }
__device__ __forceinline__ void wg_fence() { asm volatile("wgmma.fence.sync.aligned;" ::: "memory"); }
__device__ __forceinline__ void wg_commit() { asm volatile("wgmma.commit_group.sync.aligned;" ::: "memory"); }
template <int N> __device__ __forceinline__ void wg_wait() { asm volatile("wgmma.wait_group.sync.aligned %0;" ::"n"(N) : "memory"); }
__device__ __forceinline__ uint64_t make_desc(uint32_t addr, uint32_t lbo, uint32_t sbo) {
  return (uint64_t)((addr & 0x3FFFF) >> 4) | ((uint64_t)(lbo >> 4) << 16) | ((uint64_t)(sbo >> 4) << 32) | (1ull << 62);
}
__device__ __forceinline__ float bfr(float x) { return __bfloat162float(__float2bfloat16_rn(x)); }
__device__ __forceinline__ uint32_t pack2(float lo, float hi) {
  __nv_bfloat162 v = __floats2bfloat162_rn(lo, hi);
  return *reinterpret_cast<uint32_t*>(&v);
}
__device__ __forceinline__ float ex2f(float x) { float r; asm("ex2.approx.ftz.f32 %0, %1;" : "=f"(r) : "f"(x)); return r; }
__device__ __forceinline__ float lo_f(uint32_t v) { return __uint_as_float(v << 16); }
__device__ __forceinline__ float hi_f(uint32_t v) { return __uint_as_float(v & 0xffff0000u); }
__device__ __forceinline__ uint32_t phi2(float a0, float a1) {
  const uint32_t t2 = pack2(a0, a1);
  const float t0 = lo_f(t2), t1 = hi_f(t2);
  const float e0 = ex2f(t0 * 1.4426950408889634f), e1 = ex2f(t1 * 1.4426950408889634f);
  const float f0 = t0 > 0.f ? t0 + 1.0f : e0;
  const float f1 = t1 > 0.f ? t1 + 1.0f : e1;
  const uint32_t f2 = pack2(f0, f1);
  return pack2(lo_f(f2) + 1e-6f, hi_f(f2) + 1e-6f);
}
template <int R> __device__ __forceinline__ void fence_regs(float (&d)[R]) {
#pragma unroll
  for (int i = 0; i < R; i++) asm volatile("" : "+f"(d[i])::"memory");
}

__device__ __forceinline__ void wgmma_ss_n192_tb(float (&d)[96], uint64_t da, uint64_t db, int sc) {
  asm volatile("{\n.reg .pred p;\nsetp.ne.b32 p, %98, 0;\n"
    "wgmma.mma_async.sync.aligned.m64n192k16.f32.bf16.bf16 {%0, %1, %2, %3, %4, %5, %6, %7, %8, %9, %10, %11, %12, %13, %14, %15, %16, %17, %18, %19, %20, %21, %22, %23, %24, %25, %26, %27, %28, %29, %30, %31, %32, %33, %34, %35, %36, %37, %38, %39, %40, %41, %42, %43, %44, %45, %46, %47, %48, %49, %50, %51, %52, %53, %54, %55, %56, %57, %58, %59, %60, %61, %62, %63, %64, %65, %66, %67, %68, %69, %70, %71, %72, %73, %74, %75, %76, %77, %78, %79, %80, %81, %82, %83, %84, %85, %86, %87, %88, %89, %90, %91, %92, %93, %94, %95}, %96, %97, p, 1, 1, 0, 1;\n}\n"
    : "+f"(d[0]), "+f"(d[1]), "+f"(d[2]), "+f"(d[3]), "+f"(d[4]), "+f"(d[5]), "+f"(d[6]), "+f"(d[7]), "+f"(d[8]), "+f"(d[9]), "+f"(d[10]), "+f"(d[11]), "+f"(d[12]), "+f"(d[13]), "+f"(d[14]), "+f"(d[15]), "+f"(d[16]), "+f"(d[17]), "+f"(d[18]), "+f"(d[19]), "+f"(d[20]), "+f"(d[21]), "+f"(d[22]), "+f"(d[23]), "+f"(d[24]), "+f"(d[25]), "+f"(d[26]), "+f"(d[27]), "+f"(d[28]), "+f"(d[29]), "+f"(d[30]), "+f"(d[31]), "+f"(d[32]), "+f"(d[33]), "+f"(d[34]), "+f"(d[35]), "+f"(d[36]), "+f"(d[37]), "+f"(d[38]), "+f"(d[39]), "+f"(d[40]), "+f"(d[41]), "+f"(d[42]), "+f"(d[43]), "+f"(d[44]), "+f"(d[45]), "+f"(d[46]), "+f"(d[47]), "+f"(d[48]), "+f"(d[49]), "+f"(d[50]), "+f"(d[51]), "+f"(d[52]), "+f"(d[53]), "+f"(d[54]), "+f"(d[55]), "+f"(d[56]), "+f"(d[57]), "+f"(d[58]), "+f"(d[59]), "+f"(d[60]), "+f"(d[61]), "+f"(d[62]), "+f"(d[63]), "+f"(d[64]), "+f"(d[65]), "+f"(d[66]), "+f"(d[67]), "+f"(d[68]), "+f"(d[69]), "+f"(d[70]), "+f"(d[71]), "+f"(d[72]), "+f"(d[73]), "+f"(d[74]), "+f"(d[75]), "+f"(d[76]), "+f"(d[77]), "+f"(d[78]), "+f"(d[79]), "+f"(d[80]), "+f"(d[81]), "+f"(d[82]), "+f"(d[83]), "+f"(d[84]), "+f"(d[85]), "+f"(d[86]), "+f"(d[87]), "+f"(d[88]), "+f"(d[89]), "+f"(d[90]), "+f"(d[91]), "+f"(d[92]), "+f"(d[93]), "+f"(d[94]), "+f"(d[95])
    : "l"(da), "l"(db), "r"(sc));
}

__device__ __forceinline__ void wgmma_ss_n128_tb(float (&d)[64], uint64_t da, uint64_t db, int sc) {
  asm volatile("{\n.reg .pred p;\nsetp.ne.b32 p, %66, 0;\n"
    "wgmma.mma_async.sync.aligned.m64n128k16.f32.bf16.bf16 {%0, %1, %2, %3, %4, %5, %6, %7, %8, %9, %10, %11, %12, %13, %14, %15, %16, %17, %18, %19, %20, %21, %22, %23, %24, %25, %26, %27, %28, %29, %30, %31, %32, %33, %34, %35, %36, %37, %38, %39, %40, %41, %42, %43, %44, %45, %46, %47, %48, %49, %50, %51, %52, %53, %54, %55, %56, %57, %58, %59, %60, %61, %62, %63}, %64, %65, p, 1, 1, 0, 1;\n}\n"
    : "+f"(d[0]), "+f"(d[1]), "+f"(d[2]), "+f"(d[3]), "+f"(d[4]), "+f"(d[5]), "+f"(d[6]), "+f"(d[7]), "+f"(d[8]), "+f"(d[9]), "+f"(d[10]), "+f"(d[11]), "+f"(d[12]), "+f"(d[13]), "+f"(d[14]), "+f"(d[15]), "+f"(d[16]), "+f"(d[17]), "+f"(d[18]), "+f"(d[19]), "+f"(d[20]), "+f"(d[21]), "+f"(d[22]), "+f"(d[23]), "+f"(d[24]), "+f"(d[25]), "+f"(d[26]), "+f"(d[27]), "+f"(d[28]), "+f"(d[29]), "+f"(d[30]), "+f"(d[31]), "+f"(d[32]), "+f"(d[33]), "+f"(d[34]), "+f"(d[35]), "+f"(d[36]), "+f"(d[37]), "+f"(d[38]), "+f"(d[39]), "+f"(d[40]), "+f"(d[41]), "+f"(d[42]), "+f"(d[43]), "+f"(d[44]), "+f"(d[45]), "+f"(d[46]), "+f"(d[47]), "+f"(d[48]), "+f"(d[49]), "+f"(d[50]), "+f"(d[51]), "+f"(d[52]), "+f"(d[53]), "+f"(d[54]), "+f"(d[55]), "+f"(d[56]), "+f"(d[57]), "+f"(d[58]), "+f"(d[59]), "+f"(d[60]), "+f"(d[61]), "+f"(d[62]), "+f"(d[63])
    : "l"(da), "l"(db), "r"(sc));
}

__device__ __forceinline__ void wgmma_ss_n64_tatb(float (&d)[32], uint64_t da, uint64_t db, int sc) {
  asm volatile("{\n.reg .pred p;\nsetp.ne.b32 p, %34, 0;\n"
    "wgmma.mma_async.sync.aligned.m64n64k16.f32.bf16.bf16 {%0, %1, %2, %3, %4, %5, %6, %7, %8, %9, %10, %11, %12, %13, %14, %15, %16, %17, %18, %19, %20, %21, %22, %23, %24, %25, %26, %27, %28, %29, %30, %31}, %32, %33, p, 1, 1, 1, 1;\n}\n"
    : "+f"(d[0]), "+f"(d[1]), "+f"(d[2]), "+f"(d[3]), "+f"(d[4]), "+f"(d[5]), "+f"(d[6]), "+f"(d[7]), "+f"(d[8]), "+f"(d[9]), "+f"(d[10]), "+f"(d[11]), "+f"(d[12]), "+f"(d[13]), "+f"(d[14]), "+f"(d[15]), "+f"(d[16]), "+f"(d[17]), "+f"(d[18]), "+f"(d[19]), "+f"(d[20]), "+f"(d[21]), "+f"(d[22]), "+f"(d[23]), "+f"(d[24]), "+f"(d[25]), "+f"(d[26]), "+f"(d[27]), "+f"(d[28]), "+f"(d[29]), "+f"(d[30]), "+f"(d[31])
    : "l"(da), "l"(db), "r"(sc));
}

__device__ __forceinline__ void wgmma_ss_n8_tatb(float (&d)[4], uint64_t da, uint64_t db, int sc) {
  asm volatile("{\n.reg .pred p;\nsetp.ne.b32 p, %6, 0;\n"
    "wgmma.mma_async.sync.aligned.m64n8k16.f32.bf16.bf16 {%0, %1, %2, %3}, %4, %5, p, 1, 1, 1, 1;\n}\n"
    : "+f"(d[0]), "+f"(d[1]), "+f"(d[2]), "+f"(d[3])
    : "l"(da), "l"(db), "r"(sc));
}

__device__ __forceinline__ void wgmma_rs_n40_tb(float (&d)[20], uint32_t a0, uint32_t a1, uint32_t a2, uint32_t a3, uint64_t db, int sc) {
  asm volatile("{\n.reg .pred p;\nsetp.ne.b32 p, %25, 0;\n"
    "wgmma.mma_async.sync.aligned.m64n40k16.f32.bf16.bf16 {%0, %1, %2, %3, %4, %5, %6, %7, %8, %9, %10, %11, %12, %13, %14, %15, %16, %17, %18, %19}, {%20, %21, %22, %23}, %24, p, 1, 1, 1;\n}\n"
    : "+f"(d[0]), "+f"(d[1]), "+f"(d[2]), "+f"(d[3]), "+f"(d[4]), "+f"(d[5]), "+f"(d[6]), "+f"(d[7]), "+f"(d[8]), "+f"(d[9]), "+f"(d[10]), "+f"(d[11]), "+f"(d[12]), "+f"(d[13]), "+f"(d[14]), "+f"(d[15]), "+f"(d[16]), "+f"(d[17]), "+f"(d[18]), "+f"(d[19])
    : "r"(a0), "r"(a1), "r"(a2), "r"(a3), "l"(db), "r"(sc));
}

namespace k1 {
constexpr int BM = 256, BN = 192, BK = 64, ST = 4;
constexpr int A_BYTES = BM * BK * 2, B_BYTES = BK * BN * 2, STAGE = A_BYTES + B_BYTES;
constexpr int SMEM = ST * STAGE + 1024 + 256;
constexpr int OFF_PK = 0, OFF_V = 32768, OFF_ONES = 65536, OFF_KV = 69632, OFF_O = 81920, OFF_RED = 114688;
}

__global__ void __cluster_dims__(2, 1, 1) __launch_bounds__(384, 1)
k1_qkv_attn(const __grid_constant__ CUtensorMap tmx, const __grid_constant__ CUtensorMap tmw,
            const bf16* __restrict__ x, const bf16* __restrict__ gatew, const bf16* __restrict__ p0,
            const bf16* __restrict__ p1, const bf16* __restrict__ p2, const bf16* __restrict__ p3) {
  using namespace k1;
  extern __shared__ uint8_t smem_raw[];
  const uint32_t sbase = (smem_u32(smem_raw) + 1023) & ~1023u;
  uint8_t* sgen = smem_raw + (sbase - smem_u32(smem_raw));
  const uint32_t bars = sbase + ST * STAGE;
  const int tid = threadIdx.x, warp = tid >> 5, lane = tid & 31;
  const uint32_t rank = cluster_ctarank();
  const int cl = blockIdx.x >> 1;
  const int mt = cl >> 3;
  const int hp = ((cl & 7) << 1) + rank;
  const int m0 = mt * BM;

  if (tid == 0) {
    for (int s = 0; s < ST; s++) {
      mbar_init(bars + 8 * s, 1);
      mbar_init(bars + 8 * (ST + s), 16);
    }
    asm volatile("fence.mbarrier_init.release.cluster;" ::: "memory");
  }
  cluster_sync_all();
  pdl_launch();

  if (warp >= 8) {
    asm volatile("setmaxnreg.dec.sync.aligned.u32 40;");
    if (warp == 8 && lane == 0) {
      for (int kb = 0; kb < DM / BK; kb++) {
        const int s = kb % ST;
        mbar_wait(bars + 8 * (ST + s), ((kb / ST) & 1) ^ 1);
        const uint32_t full = bars + 8 * s;
        mbar_expect_tx(full, STAGE);
        const uint32_t sa = sbase + s * STAGE, sb = sa + A_BYTES;
        tma_load_2d_mc(sa + rank * 16384, &tmx, full, kb * BK, m0 + rank * 128, (uint16_t)3);
#pragma unroll
        for (int j = 0; j < 3; j++) tma_load_2d(sb + j * 8192, &tmw, full, j * 1024 + hp * 64, kb * BK);
      }
    } else if (warp > 8) {
      if (warp == 9 && lane < 16) {
        const size_t o = (size_t)blockIdx.x * 1024 + lane * 64;
        asm volatile("prefetch.global.L2 [%0];" ::"l"(p0 + o));
        asm volatile("prefetch.global.L2 [%0];" ::"l"(p1 + o));
        asm volatile("prefetch.global.L2 [%0];" ::"l"(p2 + o));
        asm volatile("prefetch.global.L2 [%0];" ::"l"(p3 + o));
      }
      for (int rr = warp - 9; rr < 16; rr += 3) {
        const int r = blockIdx.x * 16 + rr;
        float s = 0.f;
#pragma unroll
        for (int c = lane * 8; c < DM; c += 256) {
          const uint4 xv = __ldg(reinterpret_cast<const uint4*>(x + (size_t)r * DM + c));
          const uint4 wv = __ldg(reinterpret_cast<const uint4*>(gatew + c));
          const bf16* xp = reinterpret_cast<const bf16*>(&xv);
          const bf16* wp = reinterpret_cast<const bf16*>(&wv);
#pragma unroll
          for (int q = 0; q < 8; q++) s += bfr(__bfloat162float(xp[q]) * __bfloat162float(wp[q]));
        }
#pragma unroll
        for (int o = 16; o; o >>= 1) s += __shfl_xor_sync(0xffffffffu, s, o);
        if (lane == 0) { const float z = bfr(s); g_gate[r] = bfr(1.0f / (1.0f + ex2f(-z * 1.4426950408889634f))); }
      }
    }
    __syncwarp();
    cluster_sync_all();
  } else {
    asm volatile("setmaxnreg.inc.sync.aligned.u32 232;");
    const int wg = warp >> 2, w4 = warp & 3, g = lane >> 2, t = lane & 3;
    if (tid == 0) TS(1, 0);
    float acc[2][96];
#pragma unroll
    for (int i = 0; i < 96; i++) { acc[0][i] = 0.f; acc[1][i] = 0.f; }
    for (int kb = 0; kb < DM / BK; kb++) {
      const int s = kb % ST;
      mbar_wait(bars + 8 * s, (kb / ST) & 1);
      const uint32_t sa = sbase + s * STAGE + wg * 16384, sb = sbase + s * STAGE + A_BYTES;
      wg_fence();
#pragma unroll
      for (int ks = 0; ks < 4; ks++) {
        const uint64_t db = make_desc(sb + ks * 2048, 8192, 1024);
#pragma unroll
        for (int mb = 0; mb < 2; mb++) {
          const uint64_t da = make_desc(sa + mb * 8192 + ks * 32, 16, 1024);
          wgmma_ss_n192_tb(acc[mb], da, db, 1);
        }
      }
      wg_commit();
      if (kb > 0) {
        wg_wait<1>();
        const int sp = (kb - 1) % ST;
        if (lane == 0) { mbar_arrive_cluster(bars + 8 * (ST + sp), 0); mbar_arrive_cluster(bars + 8 * (ST + sp), 1); }
      }
    }
    wg_wait<0>();
    fence_regs(acc[0]); fence_regs(acc[1]);
    if (tid == 0) TS(1, 1);
    named_bar_sync(1, 256);

#pragma unroll
    for (int mb = 0; mb < 2; mb++) {
#pragma unroll
      for (int h = 0; h < 2; h++) {
        const int r = wg * 128 + mb * 64 + w4 * 16 + g + h * 8;
#pragma unroll
        for (int j = 0; j < 8; j++) {
          const uint32_t off = r * 128 + ((j ^ (r & 7)) << 4) + t * 4;
          const float k0 = acc[mb][4 * (8 + j) + 2 * h], k1v = acc[mb][4 * (8 + j) + 2 * h + 1];
          const float v0 = acc[mb][4 * (16 + j) + 2 * h], v1 = acc[mb][4 * (16 + j) + 2 * h + 1];
          *reinterpret_cast<uint32_t*>(sgen + OFF_PK + off) = phi2(k0, k1v);
          *reinterpret_cast<uint32_t*>(sgen + OFF_V + off) = pack2(v0, v1);
        }
      }
    }
    if (tid < 256) *reinterpret_cast<uint32_t*>(sgen + OFF_ONES + tid * 4) = 0x3F803F80u;
    fence_async_smem();
    named_bar_sync(1, 256);

    if (tid == 0) TS(1, 2);
    float* part = g_part + (size_t)(hp * 8 + mt) * 2112;
    {
      float kv[32], zz[4];
#pragma unroll
      for (int i = 0; i < 32; i++) kv[i] = 0.f;
#pragma unroll
      for (int i = 0; i < 4; i++) zz[i] = 0.f;
      wg_fence();
#pragma unroll
      for (int ks = 0; ks < 8; ks++) {
        const uint64_t da = make_desc(sbase + OFF_PK + wg * 16384 + ks * 2048, 16, 1024);
        const uint64_t db = make_desc(sbase + OFF_V + wg * 16384 + ks * 2048, 16, 1024);
        const uint64_t d1 = make_desc(sbase + OFF_ONES, 16, 0);
        wgmma_ss_n64_tatb(kv, da, db, 1);
        wgmma_ss_n8_tatb(zz, da, d1, 1);
      }
      wg_commit();
      wg_wait<0>();
      fence_regs(kv); fence_regs(zz);
      const int hh = w4 >> 1;
      float* red = reinterpret_cast<float*>(sgen + OFF_RED);
      float vals[2][4][2];
#pragma unroll
      for (int h = 0; h < 2; h++)
#pragma unroll
        for (int j = 0; j < 4; j++) {
          vals[h][j][0] = hh ? kv[4 * (4 + j) + 2 * h] : kv[4 * j + 2 * h];
          vals[h][j][1] = hh ? kv[4 * (4 + j) + 2 * h + 1] : kv[4 * j + 2 * h + 1];
        }
      if (wg == 1) {
#pragma unroll
        for (int h = 0; h < 2; h++) {
          const int d = (w4 & 1) * 16 + g + h * 8;
#pragma unroll
          for (int j = 0; j < 4; j++)
            *reinterpret_cast<float2*>(red + hh * 1056 + d * 32 + 8 * j + 2 * t) = make_float2(vals[h][j][0], vals[h][j][1]);
          if (t == 0) red[hh * 1056 + 1024 + d] = zz[2 * h];
        }
      }
      named_bar_sync(1, 256);
      if (wg == 0) {
#pragma unroll
        for (int h = 0; h < 2; h++) {
          const int d = (w4 & 1) * 16 + g + h * 8;
#pragma unroll
          for (int j = 0; j < 4; j++) {
            const float2 o = *reinterpret_cast<const float2*>(red + hh * 1056 + d * 32 + 8 * j + 2 * t);
            *reinterpret_cast<float2*>(part + hh * 1056 + d * 32 + 8 * j + 2 * t) = make_float2(vals[h][j][0] + o.x, vals[h][j][1] + o.y);
          }
          if (t == 0) part[hh * 1056 + 1024 + d] = zz[2 * h] + red[hh * 1056 + 1024 + d];
        }
        named_bar_sync(2, 128);
        if (tid == 0) { __threadfence(); atomicAdd(&g_cnt[hp], 1u); }
      }
    }
    if (tid == 0) TS(1, 3);
    uint32_t pq[2][4][4];
#pragma unroll
    for (int mb = 0; mb < 2; mb++)
#pragma unroll
      for (int kk = 0; kk < 4; kk++) {
        pq[mb][kk][0] = phi2(acc[mb][8 * kk + 0], acc[mb][8 * kk + 1]);
        pq[mb][kk][1] = phi2(acc[mb][8 * kk + 2], acc[mb][8 * kk + 3]);
        pq[mb][kk][2] = phi2(acc[mb][8 * kk + 4], acc[mb][8 * kk + 5]);
        pq[mb][kk][3] = phi2(acc[mb][8 * kk + 6], acc[mb][8 * kk + 7]);
      }
    if (tid == 0) TS(1, 4);
    if (tid == 0) {
      unsigned int v;
      int spins = 0;
      do { asm volatile("ld.acquire.gpu.global.u32 %0, [%1];" : "=r"(v) : "l"(&g_cnt[hp]) : "memory"); } while (v < 8u && ++spins < (1 << 24));
    }
    named_bar_sync(1, 256);
    {
      if (tid == 0) TS(1, 5);
      const float* pb = g_part + (size_t)(hp * 8) * 2112;
      for (int i = tid; i < 528; i += 256) {
        float4 s4 = make_float4(0.f, 0.f, 0.f, 0.f);
#pragma unroll
        for (int p = 0; p < 8; p++) {
          float4 v4 = __ldcg(reinterpret_cast<const float4*>(pb + p * 2112) + i);
          s4.x += v4.x; s4.y += v4.y; s4.z += v4.z; s4.w += v4.w;
        }
        const int hh = i / 264, rem = i - hh * 264;
        uint8_t* tile = sgen + OFF_KV + hh * 4096;
        if (rem < 256) {
          const int d = rem >> 3, e = (rem & 7) * 4;
          const uint32_t off = d * 128 + (((e >> 3) ^ (d & 7)) << 4) + (e & 7) * 2;
          *reinterpret_cast<uint2*>(tile + off) = make_uint2(pack2(s4.x, s4.y), pack2(s4.z, s4.w));
        } else {
          const int d0 = (rem - 256) * 4;
          float zv[4] = {s4.x, s4.y, s4.z, s4.w};
#pragma unroll
          for (int q = 0; q < 4; q++) {
            const int d = d0 + q;
            const uint32_t off = d * 128 + ((4 ^ (d & 7)) << 4);
            *reinterpret_cast<uint4*>(tile + off) = make_uint4(pack2(zv[q], 0.f), 0u, 0u, 0u);
          }
        }
      }
    }
    fence_async_smem();
    named_bar_sync(1, 256);
    if (tid == 0) TS(1, 6);
#pragma unroll
    for (int mb = 0; mb < 2; mb++) {
#pragma unroll
      for (int hh = 0; hh < 2; hh++) {
        float num[20];
#pragma unroll
        for (int i = 0; i < 20; i++) num[i] = 0.f;
        wg_fence();
#pragma unroll
        for (int kk = 0; kk < 2; kk++) {
          const uint64_t db = make_desc(sbase + OFF_KV + hh * 4096 + kk * 2048, 16, 1024);
          wgmma_rs_n40_tb(num, pq[mb][hh * 2 + kk][0], pq[mb][hh * 2 + kk][1], pq[mb][hh * 2 + kk][2], pq[mb][hh * 2 + kk][3], db, 1);
        }
        wg_commit();
        wg_wait<0>();
        fence_regs(num);
#pragma unroll
        for (int h = 0; h < 2; h++) {
          float den = __shfl_sync(0xffffffffu, num[16 + 2 * h], lane & ~3);
          den = bfr(bfr(den) + 1e-6f);
          const float rden = 1.0f / den;
          const int r = wg * 128 + mb * 64 + w4 * 16 + g + h * 8;
#pragma unroll
          for (int j = 0; j < 4; j++) {
            const uint32_t n2 = pack2(num[4 * j + 2 * h], num[4 * j + 2 * h + 1]);
            const float o0 = lo_f(n2) * rden, o1 = hi_f(n2) * rden;
            const uint32_t off = r * 128 + (((hh * 4 + j) ^ (r & 7)) << 4) + t * 4;
            *reinterpret_cast<uint32_t*>(sgen + OFF_O + off) = pack2(o0, o1);
          }
        }
      }
    }
    named_bar_sync(1, 256);
    if (tid == 0) TS(1, 7);
    for (int i = tid; i < 256 * 8; i += 256) {
      const int r = i >> 3, c = i & 7;
      uint4 v = *reinterpret_cast<const uint4*>(sgen + OFF_O + r * 128 + ((c ^ (r & 7)) << 4));
      *reinterpret_cast<uint4*>(g_o + (size_t)(m0 + r) * DM + hp * 64 + c * 8) = v;
    }
    if (tid == 0) TS(1, 8);
    cluster_sync_all();
  }
}

namespace k3 {
constexpr int BM = 128, BN = 128, BK = 64, ST = 5;
constexpr int A_BYTES = BM * BK * 2, B_BYTES = BK * BN * 2, STAGE = A_BYTES + B_BYTES;
constexpr int OFF_BT = ST * STAGE;
constexpr int OFF_BAR = OFF_BT + 32768;
constexpr int SMEM = OFF_BAR + 1024 + 256;
}

__global__ void __cluster_dims__(2, 1, 1) __launch_bounds__(384, 1)
k3_out(const __grid_constant__ CUtensorMap tmo, const __grid_constant__ CUtensorMap tmw,
       const __grid_constant__ CUtensorMap tmbt, const __grid_constant__ CUtensorMap tmout) {
  using namespace k3;
  extern __shared__ uint8_t smem_raw[];
  const uint32_t sbase = (smem_u32(smem_raw) + 1023) & ~1023u;
  uint8_t* sgen = smem_raw + (sbase - smem_u32(smem_raw));
  const uint32_t bars = sbase + OFF_BAR;
  const uint32_t barbt = bars + 8 * 2 * ST;
  const int tid = threadIdx.x, warp = tid >> 5, lane = tid & 31;
  const uint32_t rank = cluster_ctarank();
  const int cl = blockIdx.x >> 1;
  const int mt = cl >> 2;
  const int nt = ((cl & 3) << 1) + rank;
  const int m0 = mt * BM, n0 = nt * BN;

  if (tid == 0) {
    for (int s = 0; s < ST; s++) {
      mbar_init(bars + 8 * s, 1);
      mbar_init(bars + 8 * (ST + s), 16);
    }
    mbar_init(barbt, 1);
    asm volatile("fence.mbarrier_init.release.cluster;" ::: "memory");
  }
  cluster_sync_all();

  if (warp >= 8) {
    asm volatile("setmaxnreg.dec.sync.aligned.u32 40;");
    if (warp == 8 && lane == 0) {
      for (int kb = 0; kb < ST; kb++) {
        const uint32_t full = bars + 8 * kb;
        mbar_expect_tx(full, STAGE);
        const uint32_t sb = sbase + kb * STAGE + A_BYTES;
#pragma unroll
        for (int j = 0; j < 2; j++) tma_load_2d(sb + j * 8192, &tmw, full, n0 + j * 64, kb * BK);
      }
      pdl_wait();
      if (blockIdx.x == 0) for (int i = 0; i < 16; i++) g_cnt[i] = 0;
      for (int kb = 0; kb < DM / BK; kb++) {
        const int s = kb % ST;
        const uint32_t full = bars + 8 * s;
        const uint32_t sa = sbase + s * STAGE, sb = sa + A_BYTES;
        if (kb >= ST) {
          mbar_wait(bars + 8 * (ST + s), ((kb / ST) & 1) ^ 1);
          mbar_expect_tx(full, STAGE);
#pragma unroll
          for (int j = 0; j < 2; j++) tma_load_2d(sb + j * 8192, &tmw, full, n0 + j * 64, kb * BK);
        }
        tma_load_2d_mc(sa + rank * 8192, &tmo, full, kb * BK, m0 + rank * 64, (uint16_t)3);
        if (kb == 2) {
          mbar_expect_tx(barbt, 32768);
          tma_load_2d(sbase + OFF_BT, &tmbt, barbt, m0, n0);
          tma_load_2d(sbase + OFF_BT + 16384, &tmbt, barbt, m0 + 64, n0);
        }
      }
    }
    cluster_sync_all();
  } else {
    asm volatile("setmaxnreg.inc.sync.aligned.u32 232;");
    const int wg = warp >> 2, w4 = warp & 3, g = lane >> 2, t = lane & 3;
    if (tid == 0) TS(3, 0);
    pdl_wait();
    float gtv[2];
#pragma unroll
    for (int h = 0; h < 2; h++) gtv[h] = __ldcg(g_gate + m0 + wg * 64 + w4 * 16 + g + h * 8);
    float acc[64];
#pragma unroll
    for (int i = 0; i < 64; i++) acc[i] = 0.f;
    for (int kb = 0; kb < DM / BK; kb++) {
      const int s = kb % ST;
      mbar_wait(bars + 8 * s, (kb / ST) & 1);
      const uint32_t sa = sbase + s * STAGE + wg * 8192, sb = sbase + s * STAGE + A_BYTES;
      wg_fence();
#pragma unroll
      for (int ks = 0; ks < 4; ks++) {
        const uint64_t db = make_desc(sb + ks * 2048, 8192, 1024);
        const uint64_t da = make_desc(sa + ks * 32, 16, 1024);
        wgmma_ss_n128_tb(acc, da, db, 1);
      }
      wg_commit();
      if (kb > 0) {
        wg_wait<1>();
        const int sp = (kb - 1) % ST;
        if (lane == 0) { mbar_arrive_cluster(bars + 8 * (ST + sp), 0); mbar_arrive_cluster(bars + 8 * (ST + sp), 1); }
      }
    }
    wg_wait<0>();
    fence_regs(acc);
    if (tid == 0) TS(3, 1);
    named_bar_sync(1, 256);
    mbar_wait(barbt, 0);
#pragma unroll
    for (int h = 0; h < 2; h++) {
      const int rl = wg * 64 + w4 * 16 + g + h * 8;
      const float gt = gtv[h];
      const float omg = bfr(1.0f - gt);
      const uint8_t* bt = sgen + OFF_BT + wg * 16384;
      const int ll = rl & 63;
#pragma unroll
      for (int j = 0; j < 16; j++) {
        const int c = 8 * j + 2 * t;
        const float b0 = __bfloat162float(*reinterpret_cast<const bf16*>(bt + c * 128 + (((ll >> 3) ^ (c & 7)) << 4) + (ll & 7) * 2));
        const float b1 = __bfloat162float(*reinterpret_cast<const bf16*>(bt + (c + 1) * 128 + (((ll >> 3) ^ ((c + 1) & 7)) << 4) + (ll & 7) * 2));
        const uint32_t a2 = pack2(acc[4 * j + 2 * h], acc[4 * j + 2 * h + 1]);
        const float o0 = bfr(gt * lo_f(a2)) + bfr(omg * b0);
        const float o1 = bfr(gt * hi_f(a2)) + bfr(omg * b1);
        *reinterpret_cast<uint32_t*>(sgen + (j >> 3) * 16384 + rl * 128 + (((j & 7) ^ (rl & 7)) << 4) + t * 4) = pack2(o0, o1);
      }
    }
    fence_async_smem();
    if (tid == 0) TS(3, 2);
    named_bar_sync(2 + wg, 128);
    if ((tid & 127) == 0) {
#pragma unroll
      for (int j = 0; j < 2; j++)
        asm volatile("cp.async.bulk.tensor.2d.global.shared::cta.bulk_group [%0, {%2, %3}], [%1];" ::"l"(&tmout),
                     "r"(sbase + j * 16384 + wg * 8192), "r"(n0 + j * 64), "r"(m0 + wg * 64) : "memory");
      asm volatile("cp.async.bulk.commit_group;" ::: "memory");
      asm volatile("cp.async.bulk.wait_group.read 0;" ::: "memory");
      if (tid == 0) TS(3, 3);
    }
    cluster_sync_all();
  }
}

__device__ __align__(1024) bf16 g_bT[DM * SEQ];
constexpr int KOFF = 2048 + 16;
constexpr int KSZ = 2112;
constexpr int KCH = 2 * KSZ + 16;

__device__ __forceinline__ void mma_bf16(float (&d)[4], uint32_t a0, uint32_t a1, uint32_t a2, uint32_t a3, uint32_t b0, uint32_t b1) {
  asm volatile("mma.sync.aligned.m16n8k16.row.col.f32.bf16.bf16.f32 {%0,%1,%2,%3}, {%4,%5,%6,%7}, {%8,%9}, {%0,%1,%2,%3};"
               : "+f"(d[0]), "+f"(d[1]), "+f"(d[2]), "+f"(d[3]) : "r"(a0), "r"(a1), "r"(a2), "r"(a3), "r"(b0), "r"(b1));
}
__device__ __forceinline__ void mma_f16(float (&d)[4], uint32_t a0, uint32_t a1, uint32_t a2, uint32_t a3, uint32_t b0, uint32_t b1) {
  asm volatile("mma.sync.aligned.m16n8k16.row.col.f32.f16.f16.f32 {%0,%1,%2,%3}, {%4,%5,%6,%7}, {%8,%9}, {%0,%1,%2,%3};"
               : "+f"(d[0]), "+f"(d[1]), "+f"(d[2]), "+f"(d[3]) : "r"(a0), "r"(a1), "r"(a2), "r"(a3), "r"(b0), "r"(b1));
}
struct cf { float r, i; };
__device__ __forceinline__ cf cmul(cf a, cf b) { cf c; c.r = a.r * b.r - a.i * b.i; c.i = a.r * b.i + a.i * b.r; return c; }
__device__ __forceinline__ cf csq(cf a) { cf c; c.r = a.r * a.r - a.i * a.i; c.i = 2.f * a.r * a.i; return c; }
__device__ __forceinline__ cf cexpp(float ar, float ai, float p) {
  const float e = ex2f(ar * p * 1.4426950408889634f);
  const float th = ai * p;
  const float k = rintf(th * 0.15915494309189535f);
  float r = fmaf(k, -6.2831854820251465f, th);
  r = fmaf(k, 1.7484556000744e-7f, r);
  cf w; w.r = e * __cosf(r); w.i = e * __sinf(r); return w;
}
__device__ __forceinline__ uint32_t packh(float lo, float hi) {
  uint32_t r; asm("cvt.rn.f16x2.f32 %0, %1, %2;" : "=r"(r) : "f"(hi), "f"(lo)); return r;
}

namespace k2 {
constexpr int CH = 8;
constexpr int UPAD = 128;
constexpr int USZ = UPAD + SEQ;
constexpr int TSTR = 40;
constexpr int TABW = 72 * TSTR;
constexpr int PAIRW = 2 * TABW;
constexpr int P_K = 0;
constexpr int P_Q = KCH / 2;
constexpr int P_B = P_Q + 2 * 648;
constexpr int P_R = P_B + 324 + 4;
constexpr int OFF_U = 0;
constexpr int OFF_P = OFF_U + CH * USZ * 2;
constexpr int PW2 = P_R + 2048;
constexpr int SMEM = OFF_P + CH * PW2 * 4;
static_assert(PW2 >= PAIRW && (P_R % 4) == 0 && (PW2 % 4) == 0, "layout");
}

__global__ void __launch_bounds__(512, 1)
k2_ssm(const bf16* __restrict__ x, const bf16* __restrict__ logAr, const bf16* __restrict__ Aim, const bf16* __restrict__ Cre,
       const bf16* __restrict__ Cim, const bf16* __restrict__ logdt, const bf16* __restrict__ Dskip) {
  using namespace k2;
  extern __shared__ __align__(16) uint8_t sm[];
  const int tid = threadIdx.x, warp = tid >> 5, lane = tid & 31, g = lane >> 2, t = lane & 3;
  const int ch = warp >> 1, half = warp & 1, l64 = half * 32 + lane;
  const int d0 = blockIdx.x * CH;
  bf16* us = reinterpret_cast<bf16*>(sm + OFF_U);
  uint32_t* pw = reinterpret_cast<uint32_t*>(sm + OFF_P) + ch * PW2;
  if (tid == 0) TS(2, 0);
  pdl_launch();

  const int d = d0 + ch;
  bf16 p_la[2], p_ai[2], p_cr[2], p_ci[2];
#pragma unroll
  for (int c = 0; c < 2; c++) {
    const int idx = d * NMODE + half * 64 + c * 32 + lane;
    p_la[c] = logAr[idx]; p_ai[c] = Aim[idx]; p_cr[c] = Cre[idx]; p_ci[c] = Cim[idx];
  }
  const bf16 p_dt = logdt[d];
  asm volatile("" ::: "memory");
  uint4 uv[2][2];
#pragma unroll
  for (int it = 0; it < 2; it++) {
    const int l = 2 * (tid + it * 512);
    uv[it][0] = __ldg(reinterpret_cast<const uint4*>(x + (size_t)l * DM + d0));
    uv[it][1] = __ldg(reinterpret_cast<const uint4*>(x + (size_t)(l + 1) * DM + d0));
  }

  float acc[5][4];
#pragma unroll
  for (int a = 0; a < 5; a++)
#pragma unroll
    for (int b = 0; b < 4; b++) acc[a][b] = 0.f;
  float last = 0.f, scale;
  {
    const float dt = bfr(ex2f(__bfloat162float(p_dt) * 1.4426950408889634f));
    float cr[2], ci[2], arr[2], aii[2];
#pragma unroll
    for (int c = 0; c < 2; c++) {
      arr[c] = -bfr(ex2f(__bfloat162float(p_la[c]) * 1.4426950408889634f)) * dt;
      aii[c] = __bfloat162float(p_ai[c]) * dt;
      cr[c] = __bfloat162float(p_cr[c]) * dt;
      ci[c] = __bfloat162float(p_ci[c]) * dt;
    }
    float mx = fmaxf(fmaxf(fabsf(cr[0]), fabsf(ci[0])), fmaxf(fabsf(cr[1]), fabsf(ci[1])));
#pragma unroll
    for (int o = 16; o; o >>= 1) mx = fmaxf(mx, __shfl_xor_sync(0xffffffffu, mx, o));
    {
      int e = (int)((__float_as_uint(mx) >> 23) & 255u) + 1;
      e = e < 32 ? 32 : (e > 220 ? 220 : e);
      scale = __uint_as_float((uint32_t)e << 23);
    }
    const float iscale = __uint_as_float((uint32_t)(254 - ((__float_as_uint(scale) >> 23) & 255u)) << 23);
    uint32_t* tab = pw + half * TABW;
    if (tid == 0) TS(2, 5);
#pragma unroll 1
    for (int c = 0; c < 2; c++) {
      const float ar = arr[c], ai = aii[c];
      cf C; C.r = cr[c] * iscale; C.i = ci[c] * iscale;
      const cf W1 = cexpp(ar, ai, 1.f), W16 = cexpp(ar, ai, 16.f), W256 = cexpp(ar, ai, 256.f);
      const cf W512 = csq(W256), W1024 = csq(W512);
      const cf W1536 = cmul(W1024, W512);
      {
        const cf w2048 = csq(W1024);
        last += cr[c] * w2048.r - ci[c] * w2048.i;
      }
      uint32_t* tp = tab + lane;
      {
        cf xa = C;
#pragma unroll
        for (int i = 0; i < 16; i++) {
          const uint32_t pk = packh(xa.r, -xa.i);
          tp[i * TSTR] = pk;
          if ((i & 1) == 0) {
            tp[(16 + i / 2) * TSTR] = pk;
            const cf xb = cmul(xa, W256);
            tp[(24 + i / 2) * TSTR] = packh(xb.r, -xb.i);
          }
          xa = cmul(xa, W16);
        }
      }
      {
        cf y; y.r = 1.f; y.i = 0.f;
        const cf W528 = cmul(W512, W16);
        const cf WA16 = cmul(W1024, W16), WB16 = cmul(W1536, W16);
#pragma unroll
        for (int j = 0; j < 16; j++) {
          tp[(32 + j) * TSTR] = packh(y.r, y.i);
          if ((j & 1) == 0) { const cf z = cmul(y, W256); tp[(48 + j / 2) * TSTR] = packh(z.r, z.i); }
          if ((j & 3) == 0) {
            const cf z0 = cmul(y, W512), z1 = cmul(y, W528);
            tp[(56 + j / 4) * TSTR] = packh(z0.r, z0.i);
            tp[(60 + j / 4) * TSTR] = packh(z1.r, z1.i);
          }
          if ((j & 7) == 0) {
            const cf z0 = cmul(y, W1024), z1 = cmul(y, WA16), z2 = cmul(y, W1536), z3 = cmul(y, WB16);
            tp[(64 + j / 8) * TSTR] = packh(z0.r, z0.i);
            tp[(66 + j / 8) * TSTR] = packh(z1.r, z1.i);
            tp[(68 + j / 8) * TSTR] = packh(z2.r, z2.i);
            tp[(70 + j / 8) * TSTR] = packh(z3.r, z3.i);
          }
          y = cmul(y, W1);
        }
      }
      __syncwarp();
      if (tid == 0) TS(2, 6 + 2 * c);
#pragma unroll
      for (int ks4 = 0; ks4 < 4; ks4++) {
        const uint32_t* fp = tab + 8 * ks4 + 2 * t;
        const uint2 xa0 = *reinterpret_cast<const uint2*>(fp + g * TSTR), xa1 = *reinterpret_cast<const uint2*>(fp + (g + 8) * TSTR);
        const uint2 xb0 = *reinterpret_cast<const uint2*>(fp + (16 + g) * TSTR), xb1 = *reinterpret_cast<const uint2*>(fp + (24 + g) * TSTR);
        const uint2 y1 = *reinterpret_cast<const uint2*>(fp + (32 + g) * TSTR), y2 = *reinterpret_cast<const uint2*>(fp + (40 + g) * TSTR);
        const uint2 y3 = *reinterpret_cast<const uint2*>(fp + (48 + g) * TSTR), y4 = *reinterpret_cast<const uint2*>(fp + (56 + g) * TSTR);
        const uint2 y5 = *reinterpret_cast<const uint2*>(fp + (64 + g) * TSTR);
        mma_f16(acc[0], xa0.x, xa1.x, xa0.y, xa1.y, y1.x, y1.y);
        mma_f16(acc[1], xa0.x, xa1.x, xa0.y, xa1.y, y2.x, y2.y);
        mma_f16(acc[2], xa0.x, xa1.x, xa0.y, xa1.y, y3.x, y3.y);
        mma_f16(acc[3], xb0.x, xb1.x, xb0.y, xb1.y, y4.x, y4.y);
        mma_f16(acc[4], xb0.x, xb1.x, xb0.y, xb1.y, y5.x, y5.y);
      }
      __syncwarp();
      if (tid == 0) TS(2, 7 + 2 * c);
    }
  }
  if (tid == 0) TS(2, 1);
  if (tid < CH * UPAD / 2) {
    const int c = tid / (UPAD / 2), o = tid % (UPAD / 2);
    reinterpret_cast<uint32_t*>(us + c * USZ)[o] = 0u;
  }
#pragma unroll
  for (int it = 0; it < 2; it++) {
    const int l = 2 * (tid + it * 512);
    const int e = l & 15;
    const int pe = ((e & 7) >> 1) * 4 + (e >> 3) * 2;
    const int pos = UPAD + (l & ~15) + pe;
    const uint32_t a[4] = {uv[it][0].x, uv[it][0].y, uv[it][0].z, uv[it][0].w};
    const uint32_t b[4] = {uv[it][1].x, uv[it][1].y, uv[it][1].z, uv[it][1].w};
#pragma unroll
    for (int c = 0; c < 4; c++) {
      *reinterpret_cast<uint32_t*>(us + (2 * c) * USZ + pos) = __byte_perm(a[c], b[c], 0x5410);
      *reinterpret_cast<uint32_t*>(us + (2 * c + 1) * USZ + pos) = __byte_perm(a[c], b[c], 0x7632);
    }
  }
  named_bar_sync(1 + ch, 64);
  if (tid == 0) TS(2, 10);
  float* kqp = reinterpret_cast<float*>(pw + P_Q);
  {
    float* kq = kqp + half * 648;
    const float sc2 = 2.f * scale;
#pragma unroll
    for (int h = 0; h < 2; h++) {
      const int i = g + 8 * h;
      *reinterpret_cast<float2*>(kq + 16 * i + 2 * t) = make_float2(sc2 * acc[0][2 * h], sc2 * acc[0][2 * h + 1]);
      *reinterpret_cast<float2*>(kq + 16 * i + 8 + 2 * t) = make_float2(sc2 * acc[1][2 * h], sc2 * acc[1][2 * h + 1]);
      *reinterpret_cast<float2*>(kq + 256 + 8 * i + 2 * t) = make_float2(sc2 * acc[2][2 * h], sc2 * acc[2][2 * h + 1]);
      *reinterpret_cast<float2*>(kq + 384 + 8 * i + 2 * t) = make_float2(sc2 * acc[3][2 * h], sc2 * acc[3][2 * h + 1]);
      *reinterpret_cast<float2*>(kq + 512 + 4 * i + 64 * (t >> 1) + 2 * (t & 1)) = make_float2(sc2 * acc[4][2 * h], sc2 * acc[4][2 * h + 1]);
    }
#pragma unroll
    for (int o = 16; o; o >>= 1) last += __shfl_xor_sync(0xffffffffu, last, o);
    if (lane == 0) kq[640] = 2.f * last;
  }
  named_bar_sync(1 + ch, 64);
  if (tid == 0) TS(2, 11);
  bf16* kb = reinterpret_cast<bf16*>(pw + P_B);
  for (int i = l64; i < 324; i += 64) {
    const float2 a = *reinterpret_cast<const float2*>(kqp + 2 * i), b = *reinterpret_cast<const float2*>(kqp + 648 + 2 * i);
    pw[P_B + i] = pack2(a.x + b.x, a.y + b.y);
  }
  named_bar_sync(1 + ch, 64);
  {
    if (tid == 0) TS(2, 12);
    const uint16_t* kh = reinterpret_cast<const uint16_t*>(kb);
    for (int v = l64; v < KSZ / 8; v += 64) {
      uint32_t kv[9];
      const int xt = KOFF - 8 * v;
      if (xt > 2048 || xt < 0) {
#pragma unroll
        for (int q = 0; q < 9; q++) kv[q] = 0u;
      } else if (xt > 1024) {
        const int m = xt >> 3;
        const uint32_t A = kh[384 + m], B = kh[383 + m], T = (m & 1) ? B : A;
        kv[0] = A; kv[1] = A; kv[2] = A; kv[3] = A; kv[4] = T; kv[5] = B; kv[6] = B; kv[7] = B; kv[8] = B;
      } else if (xt > 512) {
        const int m = xt >> 2;
        const uint32_t A = kh[256 + m], B = kh[255 + m], C = kh[254 + m];
        kv[0] = A; kv[1] = A; kv[2] = A; kv[3] = B; kv[4] = B; kv[5] = B; kv[6] = C; kv[7] = C; kv[8] = C;
      } else if (xt > 256) {
        const int m = xt >> 1;
        const uint32_t A = kh[128 + m], B = kh[127 + m], C = kh[126 + m], E = kh[125 + m], F4 = kh[124 + m];
        kv[0] = A; kv[1] = A; kv[2] = B; kv[3] = C; kv[4] = C; kv[5] = C; kv[6] = E; kv[7] = F4; kv[8] = F4;
      } else {
#pragma unroll
        for (int q = 0; q < 9; q++) kv[q] = xt - q >= 0 ? (uint32_t)kh[xt - q] : 0u;
      }
      *reinterpret_cast<uint4*>(pw + P_K + 4 * v) =
          make_uint4(kv[0] | (kv[1] << 16), kv[2] | (kv[3] << 16), kv[4] | (kv[5] << 16), kv[6] | (kv[7] << 16));
      *reinterpret_cast<uint4*>(pw + P_K + (KSZ + 16) / 2 + 4 * v) =
          make_uint4(kv[1] | (kv[2] << 16), kv[3] | (kv[4] << 16), kv[5] | (kv[6] << 16), kv[7] | (kv[8] << 16));
    }
  }
  if (tid == 0) TS(2, 13);
  __syncthreads();
  if (tid == 0) TS(2, 2);

  float D[16][4];
#pragma unroll
  for (int j = 0; j < 16; j++)
#pragma unroll
    for (int q = 0; q < 4; q++) D[j][q] = 0.f;
  const bf16* uc = us + ch * USZ + UPAD;
  {
    const uint32_t* fbase = pw + P_K + ((g & 1) ? (KSZ + 16) / 2 : 0) + ((KOFF - g + 2 * t) >> 1);
    for (int r = half * 4; r < half * 4 + 4; r++) {
      uint32_t B[16][2];
#pragma unroll
      for (int j = 0; j < 16; j++) {
        const uint2 v = *reinterpret_cast<const uint2*>(uc + 16 * (8 * j - r + g) + 4 * t);
        B[j][0] = v.x; B[j][1] = v.y;
      }
      uint32_t fm1 = fbase[-4 * (2 * r - 1)];
#pragma unroll
      for (int k = 0; k < 16; k++) {
        const int dl = 8 * k + r;
        const uint32_t f0 = fbase[-4 * (2 * dl)];
        const uint32_t f1 = fbase[-4 * (2 * dl + 1)];
        if (k > 0) fm1 = fbase[-4 * (2 * dl - 1)];
#pragma unroll
        for (int j = k; j < 16; j++) mma_bf16(D[j], f0, f1, fm1, f0, B[j - k][0], B[j - k][1]);
      }
    }
  }
  if (tid == 0) TS(2, 3);
  float* red = reinterpret_cast<float*>(pw + P_R);
#pragma unroll
  for (int j = 0; j < 8; j++) {
    const int jo = half ? j : j + 8;
    *reinterpret_cast<float4*>(red + (jo * 32 + lane) * 4) =
        make_float4(half ? D[j][0] : D[j + 8][0], half ? D[j][1] : D[j + 8][1], half ? D[j][2] : D[j + 8][2], half ? D[j][3] : D[j + 8][3]);
  }
  named_bar_sync(1 + ch, 64);
  {
    const float dsk = __bfloat162float(Dskip[d]);
    uint16_t* ys = reinterpret_cast<uint16_t*>(pw + P_K);
#pragma unroll
    for (int j = 0; j < 8; j++) {
      const int jm = half ? j + 8 : j;
      const float4 o = *reinterpret_cast<const float4*>(red + (jm * 32 + lane) * 4);
      const float dd[4] = {(half ? D[j + 8][0] : D[j][0]) + o.x, (half ? D[j + 8][1] : D[j][1]) + o.y,
                           (half ? D[j + 8][2] : D[j][2]) + o.z, (half ? D[j + 8][3] : D[j][3]) + o.w};
#pragma unroll
      for (int q = 0; q < 4; q++) {
        const int a = 8 * jm + 2 * t + (q & 1), bb = g + (q >> 1) * 8;
        const int pe = ((bb & 7) >> 1) * 4 + (bb >> 3) * 2 + (bb & 1);
        const float uvv = __bfloat162float(uc[16 * a + pe]);
        const float y = bfr(dd[q]) + bfr(uvv * dsk);
        ys[16 * a + bb] = (uint16_t)(__float_as_uint(bfr(y)) >> 16);
      }
    }
    __syncwarp();
    bf16* dst = g_bT + (size_t)d * SEQ + half * 1024;
#pragma unroll
    for (int i = 0; i < 4; i++) {
      const uint4 v = *reinterpret_cast<const uint4*>(ys + half * 1024 + (i * 32 + lane) * 8);
      *reinterpret_cast<uint4*>(dst + (i * 32 + lane) * 8) = v;
    }
  }
  if (tid == 0) TS(2, 4);
  if (tid == 0) pdl_wait();
}

typedef CUresult (*EncodeFn)(CUtensorMap*, CUtensorMapDataType, cuuint32_t, void*, const cuuint64_t*, const cuuint64_t*,
                             const cuuint32_t*, const cuuint32_t*, CUtensorMapInterleave, CUtensorMapSwizzle,
                             CUtensorMapL2promotion, CUtensorMapFloatOOBfill);

static void make_map(EncodeFn enc, CUtensorMap* m, void* ptr, uint64_t inner, uint64_t outer, uint32_t bi, uint32_t bo) {
  cuuint64_t dims[2] = {inner, outer};
  cuuint64_t strides[1] = {inner * 2};
  cuuint32_t box[2] = {bi, bo};
  cuuint32_t es[2] = {1, 1};
  enc(m, CU_TENSOR_MAP_DATA_TYPE_BFLOAT16, 2, ptr, dims, strides, box, es, CU_TENSOR_MAP_INTERLEAVE_NONE,
      CU_TENSOR_MAP_SWIZZLE_128B, CU_TENSOR_MAP_L2_PROMOTION_L2_256B, CU_TENSOR_MAP_FLOAT_OOB_FILL_NONE);
}

extern "C" void kernel_launch(void* const* d_in, const int* in_sizes, int n_in, void* d_out, int out_size) {
  const bf16* x = (const bf16*)d_in[0];
  const bf16* wqkv = (const bf16*)d_in[1];
  const bf16* wo = (const bf16*)d_in[2];
  const bf16* logAr = (const bf16*)d_in[4];
  const bf16* Aim = (const bf16*)d_in[5];
  const bf16* Cre = (const bf16*)d_in[6];
  const bf16* Cim = (const bf16*)d_in[7];
  const bf16* logdt = (const bf16*)d_in[8];
  const bf16* Dskip = (const bf16*)d_in[9];
  const bf16* gatew = (const bf16*)d_in[10];

  static EncodeFn enc = nullptr;
  static void* p_o = nullptr;
  static void* p_bT = nullptr;
  if (!enc) {
    void* fn = nullptr;
    cudaDriverEntryPointQueryResult qr;
    cudaGetDriverEntryPoint("cuTensorMapEncodeTiled", &fn, cudaEnableDefault, &qr);
    enc = (EncodeFn)fn;
    cudaGetSymbolAddress(&p_o, g_o);
    cudaGetSymbolAddress(&p_bT, g_bT);
    cudaFuncSetAttribute(k1_qkv_attn, cudaFuncAttributeMaxDynamicSharedMemorySize, k1::SMEM);
    cudaFuncSetAttribute(k2_ssm, cudaFuncAttributeMaxDynamicSharedMemorySize, k2::SMEM);
    cudaFuncSetAttribute(k3_out, cudaFuncAttributeMaxDynamicSharedMemorySize, k3::SMEM);
  }
  CUtensorMap tmx, tmw, tmo, tmwo, tmbt, tmout;
  make_map(enc, &tmx, (void*)x, 1024, 2048, 64, 128);
  make_map(enc, &tmw, (void*)wqkv, 3072, 1024, 64, 64);
  make_map(enc, &tmo, p_o, 1024, 2048, 64, 64);
  make_map(enc, &tmwo, (void*)wo, 1024, 1024, 64, 64);
  make_map(enc, &tmbt, p_bT, 2048, 1024, 64, 128);
  make_map(enc, &tmout, d_out, 1024, 2048, 64, 64);

  k1_qkv_attn<<<128, 384, k1::SMEM>>>(tmx, tmw, x, gatew, logAr, Aim, Cre, Cim);
  cudaLaunchAttribute at[1];
  at[0].id = cudaLaunchAttributeProgrammaticStreamSerialization;
  at[0].val.programmaticStreamSerializationAllowed = 1;
  cudaLaunchConfig_t cfg = {};
  cfg.stream = cudaStreamPerThread; cfg.attrs = at; cfg.numAttrs = 1;
  cfg.gridDim = dim3(128); cfg.blockDim = dim3(512); cfg.dynamicSmemBytes = k2::SMEM;
  cudaLaunchKernelEx(&cfg, k2_ssm, x, logAr, Aim, Cre, Cim, logdt, Dskip);
  cfg.blockDim = dim3(384); cfg.dynamicSmemBytes = k3::SMEM;
  cudaLaunchKernelEx(&cfg, k3_out, tmo, tmwo, tmbt, tmout);
}
```
